```python
import torch

def _softmax(x, axis=-1):
    return torch.softmax(x, dim=axis)

def _gelu(x):
    return torch.nn.functional.gelu(x, approximate='tanh')

def _silu(x):
    return torch.nn.functional.silu(x)

def _sigmoid(x):
    return torch.sigmoid(x)

def _layernorm(x, axis=-1, eps=1e-05):
    m = x.mean(dim=axis, keepdim=True)
    v = x.var(dim=axis, keepdim=True, unbiased=False)
    return (x - m) / torch.sqrt(v + eps)

def _scatter_add(tgt, idx, src, axis=0):
    return tgt.clone().index_add_(axis, idx, src)

def _segment_sum(src, seg, n):
    out = torch.zeros((n,) + src.shape[1:], dtype=src.dtype)
    return out.index_add_(0, seg, src)

def _pad(x, pw):
    flat = tuple((v for pair in reversed(pw) for v in pair))
    return torch.nn.functional.pad(x, flat)
kernel_name = 'gated_mix__memory_aug_recurrent_mem_tr__glu_gated_bilinear__prompt'

def setup_inputs():

    _w = lambda a: (lambda t: t.to(torch.bfloat16) if t.is_floating_point() else t)(torch.as_tensor(a))

    def _A_setup():
        B, S, Dm = (1, 2048, 640)
        H, Dh = (32, 128)
        M, seg = (8, 32)
        seg = min(seg, S)
        S = S // seg * seg
        return {'x': _w((lambda *s: torch.randn(*s, dtype=torch.bfloat16) * 0.05)(B, S, Dm)), 'mem0': _w((lambda *s: torch.randn(*s, dtype=torch.bfloat16) * 0.4)(B, M, Dm)), 'Wq': _w((lambda *s: torch.randn(*s, dtype=torch.bfloat16) * 6.4)(Dm, H, Dh) * Dm ** (-0.5)), 'Wk': _w((lambda *s: torch.randn(*s, dtype=torch.bfloat16) * 6.4)(Dm, H, Dh) * Dm ** (-0.5)), 'Wv': _w((lambda *s: torch.randn(*s, dtype=torch.bfloat16) * 0.4)(Dm, H, Dh) * Dm ** (-0.5)), 'Wo': _w((lambda *s: torch.randn(*s, dtype=torch.bfloat16) * 0.4)(H, Dh, Dm) * (H * Dh) ** (-0.5)), 'seg_len': seg}
    _A_in = _A_setup()

    def _B_setup():
        B, S, D, F = (1, 2048, 640, 1728)
        return {'x': _w((lambda *s: torch.randn(*s, dtype=torch.bfloat16) * 0.05)(B, S, D)), 'w_gate': _w((lambda *s: torch.randn(*s, dtype=torch.bfloat16) * 1.6)(D, F) * D ** (-0.5)), 'w_up': _w((lambda *s: torch.randn(*s, dtype=torch.bfloat16) * 1.6)(D, F) * D ** (-0.5)), 'w_down': _w((lambda *s: torch.randn(*s, dtype=torch.bfloat16) * 1.6)(F, D) * F ** (-0.5))}
    _B_in = _B_setup()
    return {'A_x': _A_in['x'], 'A_mem0': _A_in['mem0'], 'A_Wq': _A_in['Wq'], 'A_Wk': _A_in['Wk'], 'A_Wv': _A_in['Wv'], 'A_Wo': _A_in['Wo'], 'A_seg_len': _A_in['seg_len'], 'B_x': _B_in['x'], 'B_w_gate': _B_in['w_gate'], 'B_w_up': _B_in['w_up'], 'B_w_down': _B_in['w_down'], 'gate_w': _w((lambda *s: torch.randn(*s, dtype=torch.bfloat16) * 0.05)(640) * 16.0)}

def reference(A_x, A_mem0, A_Wq, A_Wk, A_Wv, A_Wo, A_seg_len, B_x, B_w_gate, B_w_up, B_w_down, gate_w):

    def _A_ref(x, mem0, Wq, Wk, Wv, Wo, seg_len):
        B, S, Dm = x.shape
        H, Dh = (Wq.shape[1], Wq.shape[2])
        M = mem0.shape[1]
        scale = Dh ** (-0.5)
        n_seg = S // seg_len
        L = M + seg_len
        idx = torch.arange(L)
        mask = (idx[:, None] < M) | (idx[:, None] >= idx[None, :])
        mem = mem0
        outs = []
        for s in range(n_seg):
            xs = x[:, s * seg_len:(s + 1) * seg_len, :].clone()
            h = torch.concatenate([mem, xs], axis=1)
            q = torch.einsum('btd,dhe->bhte', h, Wq)
            k = torch.einsum('btd,dhe->bhte', h, Wk)
            v = torch.einsum('btd,dhe->bhte', h, Wv)
            scores = torch.einsum('bhqe,bhke->bhqk', q, k) * scale
            scores = torch.where(mask[None, None], scores, -1000000000.0)
            p = _softmax(scores, axis=-1)
            o = torch.einsum('bhqk,bhke->bhqe', p, v)
            o = torch.einsum('bhte,hed->btd', o, Wo)
            mem = o[:, :M, :].clone()
            outs.append(o[:, M:, :])
        return torch.concatenate(outs, axis=1)

    def _B_ref(x, w_gate, w_up, w_down):
        g = torch.einsum('bsd,df->bsf', x, w_gate)
        u = torch.einsum('bsd,df->bsf', x, w_up)
        h = g * u
        return torch.einsum('bsf,fd->bsd', h, w_down)
    x = A_x
    g = _sigmoid((x * gate_w).sum(-1, keepdims=True))
    a = _A_ref(x, A_mem0, A_Wq, A_Wk, A_Wv, A_Wo, A_seg_len)
    b = _B_ref(x, B_w_gate, B_w_up, B_w_down)
    return g * a + (1 - g) * b
```

```cpp
#include <cuda_runtime.h>
#include <cuda_bf16.h>
#include <cuda.h>
#include <stdint.h>

typedef __nv_bfloat16 bf16;
#define DEVI __device__ __forceinline__

constexpr int DM = 640, HD = 4096, NSEG = 64, SEGROWS = 40, FF = 1728, NTOK = 2048;
constexpr int KVW = 8192;
constexpr int AHW = HD + FF;
constexpr int SPIN_LIMIT = 1 << 18;

#define spin_guard spin_guard_
DEVI void spin_guard_(int& it) { ++it; asm volatile("{ .reg .pred p; .reg .u64 z; mov.u64 z, 0; setp.ge.s32 p, %0, %1; @p st.volatile.global.u32 [z], %0; }" :: "r"(it), "n"(SPIN_LIMIT)); }
DEVI uint32_t smem_u32(const void* p) { return (uint32_t)__cvta_generic_to_shared(p); }
DEVI uint32_t mapa(uint32_t a, uint32_t r) { uint32_t o; asm volatile("mapa.shared::cluster.u32 %0, %1, %2;" : "=r"(o) : "r"(a), "r"(r)); return o; }
DEVI void mbar_init(uint32_t bar, uint32_t cnt) { asm volatile("mbarrier.init.shared::cta.b64 [%0], %1;" :: "r"(bar), "r"(cnt) : "memory"); }
DEVI void mbar_expect_tx(uint32_t bar, uint32_t bytes) { asm volatile("mbarrier.arrive.expect_tx.shared::cta.b64 _, [%0], %1;" :: "r"(bar), "r"(bytes) : "memory"); }
DEVI void mbar_arrive(uint32_t bar) { asm volatile("mbarrier.arrive.shared::cta.b64 _, [%0];" :: "r"(bar) : "memory"); }
#define mbar_wait mbar_wait_
DEVI void mbar_wait_(uint32_t bar, uint32_t parity) {
    asm volatile("{ .reg .pred p, q; .reg .u32 it; .reg .u64 z; mov.u32 it, 0; mov.u64 z, 0;\n"
                 "WAIT_%=: mbarrier.try_wait.parity.shared::cta.b64 p, [%0], %1;\n"
                 "@p bra DONE_%=;\n"
                 "add.u32 it, it, 1; setp.ge.u32 q, it, %2; @q st.volatile.global.u32 [z], it;\n"
                 "bra WAIT_%=;\n"
                 "DONE_%=: }" :: "r"(bar), "r"(parity), "n"(SPIN_LIMIT) : "memory");
}
DEVI void tma2d(uint32_t dst, const CUtensorMap* m, int c0, int c1, uint32_t bar) {
    asm volatile("cp.async.bulk.tensor.2d.shared::cluster.global.mbarrier::complete_tx::bytes [%0], [%1, {%3, %4}], [%2];"
        :: "r"(dst), "l"(m), "r"(bar), "r"(c0), "r"(c1) : "memory");
}
DEVI void tma2d_mc(uint32_t dst, const CUtensorMap* m, int c0, int c1, uint32_t bar) {
    asm volatile("cp.async.bulk.tensor.2d.shared::cluster.global.mbarrier::complete_tx::bytes.multicast::cluster [%0], [%1, {%3, %4}], [%2], %5;"
        :: "r"(dst), "l"(m), "r"(bar), "r"(c0), "r"(c1), "h"((unsigned short)3) : "memory");
}
DEVI void mbar_arrive_cl(uint32_t bar) { asm volatile("mbarrier.arrive.release.cluster.shared::cluster.b64 _, [%0];" :: "r"(bar) : "memory"); }
DEVI void mbar_arrive_rlx(uint32_t bar) { asm volatile("mbarrier.arrive.relaxed.cluster.shared::cluster.b64 _, [%0];" :: "r"(bar) : "memory"); }
DEVI void fence_acq_cluster() { asm volatile("fence.acq_rel.cluster;" ::: "memory"); }
DEVI void tma_store2d(const CUtensorMap* m, uint32_t src, int c0, int c1) {
    asm volatile("cp.async.bulk.tensor.2d.global.shared::cta.bulk_group [%0, {%2, %3}], [%1];" :: "l"(m), "r"(src), "r"(c0), "r"(c1) : "memory");
}
DEVI void tma_pf2d(const CUtensorMap* m, int c0, int c1) { asm volatile("cp.async.bulk.prefetch.tensor.2d.L2.global [%0, {%1, %2}];" :: "l"(m), "r"(c0), "r"(c1) : "memory"); }
DEVI void bulk_store(void* dst, uint32_t src, uint32_t bytes) { asm volatile("cp.async.bulk.global.shared::cta.bulk_group [%0], [%1], %2;" :: "l"(dst), "r"(src), "r"(bytes) : "memory"); }
DEVI void bulk_commit() { asm volatile("cp.async.bulk.commit_group;" ::: "memory"); }
template<int N> DEVI void bulk_wait_read() { asm volatile("cp.async.bulk.wait_group.read %0;" :: "n"(N) : "memory"); }
template<int N> DEVI void bulk_wait() { asm volatile("cp.async.bulk.wait_group %0;" :: "n"(N) : "memory"); }
DEVI void fence_async_smem() { asm volatile("fence.proxy.async.shared::cta;" ::: "memory"); }
DEVI void fence_async_glb() { asm volatile("fence.proxy.async.global;" ::: "memory"); }
DEVI bool mbar_test(uint32_t bar, uint32_t parity) { uint32_t ok; asm volatile("{ .reg .pred p; mbarrier.test_wait.parity.shared::cta.b64 p, [%1], %2; selp.u32 %0, 1, 0, p; }" : "=r"(ok) : "r"(bar), "r"(parity) : "memory"); return ok; }
DEVI void fence_gpu() { asm volatile("fence.acq_rel.gpu;" ::: "memory"); }
DEVI void bar_sync(int id, int n) { asm volatile("bar.sync %0, %1;" :: "r"(id), "r"(n) : "memory"); }
DEVI void bar_arrive(int id, int n) { asm volatile("bar.arrive %0, %1;" :: "r"(id), "r"(n) : "memory"); }
DEVI void ldsm4t(uint32_t* r, uint32_t a) { asm volatile("ldmatrix.sync.aligned.m8n8.x4.trans.shared.b16 {%0,%1,%2,%3}, [%4];" : "=r"(r[0]), "=r"(r[1]), "=r"(r[2]), "=r"(r[3]) : "r"(a) : "memory"); }
DEVI void ldsm4(uint32_t* r, uint32_t a) { asm volatile("ldmatrix.sync.aligned.m8n8.x4.shared.b16 {%0,%1,%2,%3}, [%4];" : "=r"(r[0]), "=r"(r[1]), "=r"(r[2]), "=r"(r[3]) : "r"(a) : "memory"); }
DEVI void stsm4(uint32_t a, uint32_t r0, uint32_t r1, uint32_t r2, uint32_t r3) { asm volatile("stmatrix.sync.aligned.m8n8.x4.shared.b16 [%0], {%1,%2,%3,%4};" :: "r"(a), "r"(r0), "r"(r1), "r"(r2), "r"(r3) : "memory"); }
DEVI void stsm4t(uint32_t a, uint32_t r0, uint32_t r1, uint32_t r2, uint32_t r3) { asm volatile("stmatrix.sync.aligned.m8n8.x4.trans.shared.b16 [%0], {%1,%2,%3,%4};" :: "r"(a), "r"(r0), "r"(r1), "r"(r2), "r"(r3) : "memory"); }
DEVI uint32_t movm(uint32_t a) { uint32_t d; asm volatile("movmatrix.sync.aligned.m8n8.trans.b16 %0, %1;" : "=r"(d) : "r"(a)); return d; }
DEVI void mma16816(float* d, uint32_t a0, uint32_t a1, uint32_t a2, uint32_t a3, uint32_t b0, uint32_t b1) {
    asm volatile("mma.sync.aligned.m16n8k16.row.col.f32.bf16.bf16.f32 {%0,%1,%2,%3}, {%4,%5,%6,%7}, {%8,%9}, {%0,%1,%2,%3};"
        : "+f"(d[0]), "+f"(d[1]), "+f"(d[2]), "+f"(d[3]) : "r"(a0), "r"(a1), "r"(a2), "r"(a3), "r"(b0), "r"(b1));
}
DEVI void mma16816(float* d, const uint32_t* a, uint32_t b0, uint32_t b1) { mma16816(d, a[0], a[1], a[2], a[3], b0, b1); }
DEVI void mma1688(float* d, uint32_t a0, uint32_t a1, uint32_t b0) {
    asm volatile("mma.sync.aligned.m16n8k8.row.col.f32.bf16.bf16.f32 {%0,%1,%2,%3}, {%4,%5}, {%6}, {%0,%1,%2,%3};"
        : "+f"(d[0]), "+f"(d[1]), "+f"(d[2]), "+f"(d[3]) : "r"(a0), "r"(a1), "r"(b0));
}
DEVI uint32_t pack2(float lo, float hi) { uint32_t r; asm("cvt.rn.bf16x2.f32 %0, %1, %2;" : "=r"(r) : "f"(hi), "f"(lo)); return r; }
DEVI uint32_t nz(uint32_t w) { uint32_t r; asm("max.u32 %0, %1, 1;" : "=r"(r) : "r"(w)); return r; }
DEVI void sts128u(uint32_t a, uint4 v) { asm volatile("st.shared.v4.u32 [%0], {%1,%2,%3,%4};" :: "r"(a), "r"(v.x), "r"(v.y), "r"(v.z), "r"(v.w) : "memory"); }
DEVI void sts64(uint32_t a, float x, float y) { asm volatile("st.shared.v2.f32 [%0], {%1,%2};" :: "r"(a), "f"(x), "f"(y) : "memory"); }
DEVI void sts64u(uint32_t a, uint32_t x, uint32_t y) { asm volatile("st.shared.v2.u32 [%0], {%1,%2};" :: "r"(a), "r"(x), "r"(y) : "memory"); }
DEVI void sts32u(uint32_t a, uint32_t x) { asm volatile("st.shared.u32 [%0], %1;" :: "r"(a), "r"(x) : "memory"); }
DEVI uint32_t lds32u(uint32_t a) { uint32_t v; asm volatile("ld.shared.u32 %0, [%1];" : "=r"(v) : "r"(a) : "memory"); return v; }
DEVI float2 lds64(uint32_t a) { float2 v; asm volatile("ld.shared.v2.f32 {%0,%1}, [%2];" : "=f"(v.x), "=f"(v.y) : "r"(a) : "memory"); return v; }
DEVI uint4 lds128u(uint32_t a) { uint4 v; asm volatile("ld.shared.v4.u32 {%0,%1,%2,%3}, [%4];" : "=r"(v.x), "=r"(v.y), "=r"(v.z), "=r"(v.w) : "r"(a) : "memory"); return v; }
DEVI void st_async64(uint32_t dst, uint32_t x, uint32_t y, uint32_t bar) {
    asm volatile("st.async.weak.shared::cluster.mbarrier::complete_tx::bytes.v2.b32 [%0], {%1,%2}, [%3];" :: "r"(dst), "r"(x), "r"(y), "r"(bar) : "memory");
}
DEVI uint4 ld_rlx128(const void* p) { uint4 v; asm volatile("ld.relaxed.gpu.global.v4.u32 {%0,%1,%2,%3}, [%4];" : "=r"(v.x), "=r"(v.y), "=r"(v.z), "=r"(v.w) : "l"(p) : "memory"); return v; }
DEVI float4 ld_rlx128f(const void* p) { float4 v; asm volatile("ld.relaxed.gpu.global.v4.f32 {%0,%1,%2,%3}, [%4];" : "=f"(v.x), "=f"(v.y), "=f"(v.z), "=f"(v.w) : "l"(p) : "memory"); return v; }
DEVI uint32_t ld_rlx32(const void* p) { uint32_t v; asm volatile("ld.relaxed.gpu.global.u32 %0, [%1];" : "=r"(v) : "l"(p) : "memory"); return v; }
DEVI float ld_rlxf(const void* p) { float v; asm volatile("ld.relaxed.gpu.global.f32 %0, [%1];" : "=f"(v) : "l"(p) : "memory"); return v; }
DEVI uint32_t ld_acq32(const void* p) { uint32_t v; asm volatile("ld.acquire.gpu.global.u32 %0, [%1];" : "=r"(v) : "l"(p) : "memory"); return v; }
DEVI void st_rlx128(void* p, uint4 v) { asm volatile("st.relaxed.gpu.global.v4.u32 [%0], {%1,%2,%3,%4};" :: "l"(p), "r"(v.x), "r"(v.y), "r"(v.z), "r"(v.w) : "memory"); }
DEVI void st_rlx64(void* p, uint32_t x, uint32_t y) { asm volatile("st.relaxed.gpu.global.v2.u32 [%0], {%1,%2};" :: "l"(p), "r"(x), "r"(y) : "memory"); }
DEVI void st_rlx32(void* p, uint32_t x) { asm volatile("st.relaxed.gpu.global.u32 [%0], %1;" :: "l"(p), "r"(x) : "memory"); }
DEVI void st_rel32(void* p, uint32_t x) { asm volatile("st.release.gpu.global.u32 [%0], %1;" :: "l"(p), "r"(x) : "memory"); }
DEVI void red_rel_add(void* p, uint32_t x) { asm volatile("red.release.gpu.global.add.u32 [%0], %1;" :: "l"(p), "r"(x) : "memory"); }
DEVI void red_rlx_add(void* p, uint32_t x) { asm volatile("red.relaxed.gpu.global.add.u32 [%0], %1;" :: "l"(p), "r"(x) : "memory"); }
DEVI void wait_ge(const uint32_t* p, uint32_t target) { int it = 0; while (ld_acq32(p) < target) { spin_guard(it); __nanosleep(50); } }
DEVI float ex2(float x) { float y; asm("ex2.approx.ftz.f32 %0, %1;" : "=f"(y) : "f"(x)); return y; }
DEVI float rcpf(float x) { float y; asm("rcp.approx.ftz.f32 %0, %1;" : "=f"(y) : "f"(x)); return y; }
DEVI uint32_t hadd2(uint32_t a, uint32_t b) { uint32_t d; asm("add.rn.bf16x2 %0, %1, %2;" : "=r"(d) : "r"(a), "r"(b)); return d; }
DEVI uint32_t opaque(uint32_t x) { return __shfl_sync(0xffffffffu, x, threadIdx.x & 31); }
DEVI uint32_t clk() { uint32_t c; asm volatile("mov.u32 %0, %%clock;" : "=r"(c) :: "memory"); return c; }
DEVI uint32_t uni(uint32_t x) { return __shfl_sync(0xffffffffu, x, 0); }
DEVI uint32_t min4(uint4 v) { return min(min(v.x, v.y), min(v.z, v.w)); }
DEVI void wg_fence() { asm volatile("wgmma.fence.sync.aligned;" ::: "memory"); }
DEVI void wg_commit() { asm volatile("wgmma.commit_group.sync.aligned;" ::: "memory"); }
template<int N> DEVI void wg_wait() { asm volatile("wgmma.wait_group.sync.aligned %0;" :: "n"(N) : "memory"); }
DEVI uint64_t mkdesc(uint32_t addr, uint32_t lbo, uint32_t sbo) {
    return (uint64_t)((addr & 0x3FFFF) >> 4) | ((uint64_t)(lbo >> 4) << 16) | ((uint64_t)(sbo >> 4) << 32) | (1ull << 62);
}
template<int TA, int TB> DEVI void wg_ss256(float* d, uint64_t da, uint64_t db, int sc) {
    asm volatile("{ .reg .pred p; setp.ne.b32 p, %130, 0;\n wgmma.mma_async.sync.aligned.m64n256k16.f32.bf16.bf16 {%0, %1, %2, %3, %4, %5, %6, %7, %8, %9, %10, %11, %12, %13, %14, %15, %16, %17, %18, %19, %20, %21, %22, %23, %24, %25, %26, %27, %28, %29, %30, %31, %32, %33, %34, %35, %36, %37, %38, %39, %40, %41, %42, %43, %44, %45, %46, %47, %48, %49, %50, %51, %52, %53, %54, %55, %56, %57, %58, %59, %60, %61, %62, %63, %64, %65, %66, %67, %68, %69, %70, %71, %72, %73, %74, %75, %76, %77, %78, %79, %80, %81, %82, %83, %84, %85, %86, %87, %88, %89, %90, %91, %92, %93, %94, %95, %96, %97, %98, %99, %100, %101, %102, %103, %104, %105, %106, %107, %108, %109, %110, %111, %112, %113, %114, %115, %116, %117, %118, %119, %120, %121, %122, %123, %124, %125, %126, %127}, %128, %129, p, 1, 1, %131, %132; }"
        : "+f"(d[0]), "+f"(d[1]), "+f"(d[2]), "+f"(d[3]), "+f"(d[4]), "+f"(d[5]), "+f"(d[6]), "+f"(d[7]), "+f"(d[8]), "+f"(d[9]), "+f"(d[10]), "+f"(d[11]), "+f"(d[12]), "+f"(d[13]), "+f"(d[14]), "+f"(d[15]), "+f"(d[16]), "+f"(d[17]), "+f"(d[18]), "+f"(d[19]), "+f"(d[20]), "+f"(d[21]), "+f"(d[22]), "+f"(d[23]), "+f"(d[24]), "+f"(d[25]), "+f"(d[26]), "+f"(d[27]), "+f"(d[28]), "+f"(d[29]), "+f"(d[30]), "+f"(d[31]), "+f"(d[32]), "+f"(d[33]), "+f"(d[34]), "+f"(d[35]), "+f"(d[36]), "+f"(d[37]), "+f"(d[38]), "+f"(d[39]), "+f"(d[40]), "+f"(d[41]), "+f"(d[42]), "+f"(d[43]), "+f"(d[44]), "+f"(d[45]), "+f"(d[46]), "+f"(d[47]), "+f"(d[48]), "+f"(d[49]), "+f"(d[50]), "+f"(d[51]), "+f"(d[52]), "+f"(d[53]), "+f"(d[54]), "+f"(d[55]), "+f"(d[56]), "+f"(d[57]), "+f"(d[58]), "+f"(d[59]), "+f"(d[60]), "+f"(d[61]), "+f"(d[62]), "+f"(d[63]), "+f"(d[64]), "+f"(d[65]), "+f"(d[66]), "+f"(d[67]), "+f"(d[68]), "+f"(d[69]), "+f"(d[70]), "+f"(d[71]), "+f"(d[72]), "+f"(d[73]), "+f"(d[74]), "+f"(d[75]), "+f"(d[76]), "+f"(d[77]), "+f"(d[78]), "+f"(d[79]), "+f"(d[80]), "+f"(d[81]), "+f"(d[82]), "+f"(d[83]), "+f"(d[84]), "+f"(d[85]), "+f"(d[86]), "+f"(d[87]), "+f"(d[88]), "+f"(d[89]), "+f"(d[90]), "+f"(d[91]), "+f"(d[92]), "+f"(d[93]), "+f"(d[94]), "+f"(d[95]), "+f"(d[96]), "+f"(d[97]), "+f"(d[98]), "+f"(d[99]), "+f"(d[100]), "+f"(d[101]), "+f"(d[102]), "+f"(d[103]), "+f"(d[104]), "+f"(d[105]), "+f"(d[106]), "+f"(d[107]), "+f"(d[108]), "+f"(d[109]), "+f"(d[110]), "+f"(d[111]), "+f"(d[112]), "+f"(d[113]), "+f"(d[114]), "+f"(d[115]), "+f"(d[116]), "+f"(d[117]), "+f"(d[118]), "+f"(d[119]), "+f"(d[120]), "+f"(d[121]), "+f"(d[122]), "+f"(d[123]), "+f"(d[124]), "+f"(d[125]), "+f"(d[126]), "+f"(d[127])
        : "l"(da), "l"(db), "r"(sc), "n"(TA), "n"(TB));
}
DEVI void wg_rs80(float* d, const uint32_t* a, uint64_t db, int sc) {
    asm volatile("{ .reg .pred p; setp.ne.b32 p, %45, 0;\n wgmma.mma_async.sync.aligned.m64n80k16.f32.bf16.bf16 {%0, %1, %2, %3, %4, %5, %6, %7, %8, %9, %10, %11, %12, %13, %14, %15, %16, %17, %18, %19, %20, %21, %22, %23, %24, %25, %26, %27, %28, %29, %30, %31, %32, %33, %34, %35, %36, %37, %38, %39}, {%40, %41, %42, %43}, %44, p, 1, 1, 0; }"
        : "+f"(d[0]), "+f"(d[1]), "+f"(d[2]), "+f"(d[3]), "+f"(d[4]), "+f"(d[5]), "+f"(d[6]), "+f"(d[7]), "+f"(d[8]), "+f"(d[9]), "+f"(d[10]), "+f"(d[11]), "+f"(d[12]), "+f"(d[13]), "+f"(d[14]), "+f"(d[15]), "+f"(d[16]), "+f"(d[17]), "+f"(d[18]), "+f"(d[19]), "+f"(d[20]), "+f"(d[21]), "+f"(d[22]), "+f"(d[23]), "+f"(d[24]), "+f"(d[25]), "+f"(d[26]), "+f"(d[27]), "+f"(d[28]), "+f"(d[29]), "+f"(d[30]), "+f"(d[31]), "+f"(d[32]), "+f"(d[33]), "+f"(d[34]), "+f"(d[35]), "+f"(d[36]), "+f"(d[37]), "+f"(d[38]), "+f"(d[39])
        : "r"(a[0]), "r"(a[1]), "r"(a[2]), "r"(a[3]), "l"(db), "r"(sc));
}
DEVI void wg_rs128t(float* d, const uint32_t* a, uint64_t db, int sc) {
    asm volatile("{ .reg .pred p; setp.ne.b32 p, %69, 0;\n wgmma.mma_async.sync.aligned.m64n128k16.f32.bf16.bf16 {%0, %1, %2, %3, %4, %5, %6, %7, %8, %9, %10, %11, %12, %13, %14, %15, %16, %17, %18, %19, %20, %21, %22, %23, %24, %25, %26, %27, %28, %29, %30, %31, %32, %33, %34, %35, %36, %37, %38, %39, %40, %41, %42, %43, %44, %45, %46, %47, %48, %49, %50, %51, %52, %53, %54, %55, %56, %57, %58, %59, %60, %61, %62, %63}, {%64, %65, %66, %67}, %68, p, 1, 1, 1; }"
        : "+f"(d[0]), "+f"(d[1]), "+f"(d[2]), "+f"(d[3]), "+f"(d[4]), "+f"(d[5]), "+f"(d[6]), "+f"(d[7]), "+f"(d[8]), "+f"(d[9]), "+f"(d[10]), "+f"(d[11]), "+f"(d[12]), "+f"(d[13]), "+f"(d[14]), "+f"(d[15]), "+f"(d[16]), "+f"(d[17]), "+f"(d[18]), "+f"(d[19]), "+f"(d[20]), "+f"(d[21]), "+f"(d[22]), "+f"(d[23]), "+f"(d[24]), "+f"(d[25]), "+f"(d[26]), "+f"(d[27]), "+f"(d[28]), "+f"(d[29]), "+f"(d[30]), "+f"(d[31]), "+f"(d[32]), "+f"(d[33]), "+f"(d[34]), "+f"(d[35]), "+f"(d[36]), "+f"(d[37]), "+f"(d[38]), "+f"(d[39]), "+f"(d[40]), "+f"(d[41]), "+f"(d[42]), "+f"(d[43]), "+f"(d[44]), "+f"(d[45]), "+f"(d[46]), "+f"(d[47]), "+f"(d[48]), "+f"(d[49]), "+f"(d[50]), "+f"(d[51]), "+f"(d[52]), "+f"(d[53]), "+f"(d[54]), "+f"(d[55]), "+f"(d[56]), "+f"(d[57]), "+f"(d[58]), "+f"(d[59]), "+f"(d[60]), "+f"(d[61]), "+f"(d[62]), "+f"(d[63])
        : "r"(a[0]), "r"(a[1]), "r"(a[2]), "r"(a[3]), "l"(db), "r"(sc));
}
template<int TA, int TB> DEVI void wg_ss256_z(float* d, uint64_t da, uint64_t db) {
    asm volatile("{ .reg .pred p; setp.ne.b32 p, 0, 0;\n wgmma.mma_async.sync.aligned.m64n256k16.f32.bf16.bf16 {%0, %1, %2, %3, %4, %5, %6, %7, %8, %9, %10, %11, %12, %13, %14, %15, %16, %17, %18, %19, %20, %21, %22, %23, %24, %25, %26, %27, %28, %29, %30, %31, %32, %33, %34, %35, %36, %37, %38, %39, %40, %41, %42, %43, %44, %45, %46, %47, %48, %49, %50, %51, %52, %53, %54, %55, %56, %57, %58, %59, %60, %61, %62, %63, %64, %65, %66, %67, %68, %69, %70, %71, %72, %73, %74, %75, %76, %77, %78, %79, %80, %81, %82, %83, %84, %85, %86, %87, %88, %89, %90, %91, %92, %93, %94, %95, %96, %97, %98, %99, %100, %101, %102, %103, %104, %105, %106, %107, %108, %109, %110, %111, %112, %113, %114, %115, %116, %117, %118, %119, %120, %121, %122, %123, %124, %125, %126, %127}, %128, %129, p, 1, 1, %130, %131; }"
        : "=f"(d[0]), "=f"(d[1]), "=f"(d[2]), "=f"(d[3]), "=f"(d[4]), "=f"(d[5]), "=f"(d[6]), "=f"(d[7]), "=f"(d[8]), "=f"(d[9]), "=f"(d[10]), "=f"(d[11]), "=f"(d[12]), "=f"(d[13]), "=f"(d[14]), "=f"(d[15]), "=f"(d[16]), "=f"(d[17]), "=f"(d[18]), "=f"(d[19]), "=f"(d[20]), "=f"(d[21]), "=f"(d[22]), "=f"(d[23]), "=f"(d[24]), "=f"(d[25]), "=f"(d[26]), "=f"(d[27]), "=f"(d[28]), "=f"(d[29]), "=f"(d[30]), "=f"(d[31]), "=f"(d[32]), "=f"(d[33]), "=f"(d[34]), "=f"(d[35]), "=f"(d[36]), "=f"(d[37]), "=f"(d[38]), "=f"(d[39]), "=f"(d[40]), "=f"(d[41]), "=f"(d[42]), "=f"(d[43]), "=f"(d[44]), "=f"(d[45]), "=f"(d[46]), "=f"(d[47]), "=f"(d[48]), "=f"(d[49]), "=f"(d[50]), "=f"(d[51]), "=f"(d[52]), "=f"(d[53]), "=f"(d[54]), "=f"(d[55]), "=f"(d[56]), "=f"(d[57]), "=f"(d[58]), "=f"(d[59]), "=f"(d[60]), "=f"(d[61]), "=f"(d[62]), "=f"(d[63]), "=f"(d[64]), "=f"(d[65]), "=f"(d[66]), "=f"(d[67]), "=f"(d[68]), "=f"(d[69]), "=f"(d[70]), "=f"(d[71]), "=f"(d[72]), "=f"(d[73]), "=f"(d[74]), "=f"(d[75]), "=f"(d[76]), "=f"(d[77]), "=f"(d[78]), "=f"(d[79]), "=f"(d[80]), "=f"(d[81]), "=f"(d[82]), "=f"(d[83]), "=f"(d[84]), "=f"(d[85]), "=f"(d[86]), "=f"(d[87]), "=f"(d[88]), "=f"(d[89]), "=f"(d[90]), "=f"(d[91]), "=f"(d[92]), "=f"(d[93]), "=f"(d[94]), "=f"(d[95]), "=f"(d[96]), "=f"(d[97]), "=f"(d[98]), "=f"(d[99]), "=f"(d[100]), "=f"(d[101]), "=f"(d[102]), "=f"(d[103]), "=f"(d[104]), "=f"(d[105]), "=f"(d[106]), "=f"(d[107]), "=f"(d[108]), "=f"(d[109]), "=f"(d[110]), "=f"(d[111]), "=f"(d[112]), "=f"(d[113]), "=f"(d[114]), "=f"(d[115]), "=f"(d[116]), "=f"(d[117]), "=f"(d[118]), "=f"(d[119]), "=f"(d[120]), "=f"(d[121]), "=f"(d[122]), "=f"(d[123]), "=f"(d[124]), "=f"(d[125]), "=f"(d[126]), "=f"(d[127])
        : "l"(da), "l"(db), "n"(TA), "n"(TB));
}
DEVI void wg_rs80_z(float* d, const uint32_t* a, uint64_t db) {
    asm volatile("{ .reg .pred p; setp.ne.b32 p, 0, 0;\n wgmma.mma_async.sync.aligned.m64n80k16.f32.bf16.bf16 {%0, %1, %2, %3, %4, %5, %6, %7, %8, %9, %10, %11, %12, %13, %14, %15, %16, %17, %18, %19, %20, %21, %22, %23, %24, %25, %26, %27, %28, %29, %30, %31, %32, %33, %34, %35, %36, %37, %38, %39}, {%40, %41, %42, %43}, %44, p, 1, 1, 0; }"
        : "=f"(d[0]), "=f"(d[1]), "=f"(d[2]), "=f"(d[3]), "=f"(d[4]), "=f"(d[5]), "=f"(d[6]), "=f"(d[7]), "=f"(d[8]), "=f"(d[9]), "=f"(d[10]), "=f"(d[11]), "=f"(d[12]), "=f"(d[13]), "=f"(d[14]), "=f"(d[15]), "=f"(d[16]), "=f"(d[17]), "=f"(d[18]), "=f"(d[19]), "=f"(d[20]), "=f"(d[21]), "=f"(d[22]), "=f"(d[23]), "=f"(d[24]), "=f"(d[25]), "=f"(d[26]), "=f"(d[27]), "=f"(d[28]), "=f"(d[29]), "=f"(d[30]), "=f"(d[31]), "=f"(d[32]), "=f"(d[33]), "=f"(d[34]), "=f"(d[35]), "=f"(d[36]), "=f"(d[37]), "=f"(d[38]), "=f"(d[39])
        : "r"(a[0]), "r"(a[1]), "r"(a[2]), "r"(a[3]), "l"(db));
}
DEVI void wg_rs128t_z(float* d, const uint32_t* a, uint64_t db) {
    asm volatile("{ .reg .pred p; setp.ne.b32 p, 0, 0;\n wgmma.mma_async.sync.aligned.m64n128k16.f32.bf16.bf16 {%0, %1, %2, %3, %4, %5, %6, %7, %8, %9, %10, %11, %12, %13, %14, %15, %16, %17, %18, %19, %20, %21, %22, %23, %24, %25, %26, %27, %28, %29, %30, %31, %32, %33, %34, %35, %36, %37, %38, %39, %40, %41, %42, %43, %44, %45, %46, %47, %48, %49, %50, %51, %52, %53, %54, %55, %56, %57, %58, %59, %60, %61, %62, %63}, {%64, %65, %66, %67}, %68, p, 1, 1, 1; }"
        : "=f"(d[0]), "=f"(d[1]), "=f"(d[2]), "=f"(d[3]), "=f"(d[4]), "=f"(d[5]), "=f"(d[6]), "=f"(d[7]), "=f"(d[8]), "=f"(d[9]), "=f"(d[10]), "=f"(d[11]), "=f"(d[12]), "=f"(d[13]), "=f"(d[14]), "=f"(d[15]), "=f"(d[16]), "=f"(d[17]), "=f"(d[18]), "=f"(d[19]), "=f"(d[20]), "=f"(d[21]), "=f"(d[22]), "=f"(d[23]), "=f"(d[24]), "=f"(d[25]), "=f"(d[26]), "=f"(d[27]), "=f"(d[28]), "=f"(d[29]), "=f"(d[30]), "=f"(d[31]), "=f"(d[32]), "=f"(d[33]), "=f"(d[34]), "=f"(d[35]), "=f"(d[36]), "=f"(d[37]), "=f"(d[38]), "=f"(d[39]), "=f"(d[40]), "=f"(d[41]), "=f"(d[42]), "=f"(d[43]), "=f"(d[44]), "=f"(d[45]), "=f"(d[46]), "=f"(d[47]), "=f"(d[48]), "=f"(d[49]), "=f"(d[50]), "=f"(d[51]), "=f"(d[52]), "=f"(d[53]), "=f"(d[54]), "=f"(d[55]), "=f"(d[56]), "=f"(d[57]), "=f"(d[58]), "=f"(d[59]), "=f"(d[60]), "=f"(d[61]), "=f"(d[62]), "=f"(d[63])
        : "r"(a[0]), "r"(a[1]), "r"(a[2]), "r"(a[3]), "l"(db));
}

__device__ __align__(1024) bf16 g_KV[NSEG * SEGROWS * KVW];
__device__ __align__(1024) bf16 g_AH[NTOK * AHW];
constexpr int MAXSPLIT = 18;
DEVI int part_slot(int mp, int n) { return mp < 6 ? mp * 20 + n * 4 : mp == 6 ? 120 + n * 6 : 150 + n * MAXSPLIT; }
__device__ __align__(1024) bf16 g_part[(150 + 5 * MAXSPLIT) * 32768];
__device__ float g_gate[NTOK];
__device__ __align__(1024) unsigned char g_xbuf[10 * 0x200000];
struct __align__(128) Sync {
    uint32_t prog[16 * 32];
    uint32_t kv[16 * 32 * 8]; uint32_t oc[16 * 16 * 8]; uint32_t hc[16 * 8]; uint32_t done[40 * 8];
    uint32_t side[32]; uint32_t gate[32]; uint32_t queue[32]; uint32_t sidecnt[32]; uint32_t exitc[16]; uint32_t chain_exit[16];
};
__device__ Sync g_sync;

struct Maps {
    CUtensorMap x, wq, wk, wv, wg, wu, wo, wd;
    CUtensorMap ahL, ahS, kvA, kvC, kvE;
    CUtensorMap wqC, wkC, wvC, woC;
};

enum { T_KV = 0, T_UP = 1, T_QA = 2, T_OUT = 3, T_RED = 4 };
constexpr uint32_t NTASKS = 712;
__constant__ uint32_t c_tasks[NTASKS] = {
    0x02280000u, 0x02280040u, 0x02280080u, 0x022800c0u, 0x02280100u, 0x02280140u, 0x02280180u, 0x022801c0u, 0x02280200u, 0x02280240u, 0x02280280u, 0x022802c0u,
    0x02280300u, 0x02280340u, 0x02280380u, 0x022803c0u, 0x02280400u, 0x02280440u, 0x02280480u, 0x022804c0u, 0x02280500u, 0x02280540u, 0x02280580u, 0x022805c0u,
    0x02280600u, 0x02280640u, 0x02280680u, 0x022806c0u, 0x02280700u, 0x02280740u, 0x02280780u, 0x022807c0u, 0x00280001u, 0x00280041u, 0x02280004u, 0x02280044u,
    0x02280084u, 0x022800c4u, 0x02280104u, 0x02280144u, 0x02280184u, 0x022801c4u, 0x02280204u, 0x02280244u, 0x02280284u, 0x022802c4u, 0x02280304u, 0x02280344u,
    0x02280384u, 0x022803c4u, 0x02280404u, 0x02280444u, 0x02280484u, 0x022804c4u, 0x02280504u, 0x02280544u, 0x02280584u, 0x022805c4u, 0x02280604u, 0x02280644u,
    0x02280684u, 0x022806c4u, 0x02280704u, 0x02280744u, 0x02280784u, 0x022807c4u, 0x00280081u, 0x002800c1u, 0x00280101u, 0x00280141u, 0x00280181u, 0x002801c1u,
    0x00280201u, 0x00280241u, 0x00280281u, 0x002802c1u, 0x00280301u, 0x00280341u, 0x00280004u, 0x00280044u, 0x00280084u, 0x002800c4u, 0x00280104u, 0x00280144u,
    0x00280184u, 0x002801c4u, 0x00280204u, 0x00280244u, 0x00280284u, 0x002802c4u, 0x00280304u, 0x00280344u, 0x00280384u, 0x002803c4u, 0x00280404u, 0x00280444u,
    0x00280484u, 0x002804c4u, 0x00280504u, 0x00280544u, 0x00280584u, 0x002805c4u, 0x00280604u, 0x00280644u, 0x00280684u, 0x002806c4u, 0x00280704u, 0x00280744u,
    0x00280784u, 0x002807c4u, 0x006e0003u, 0x006e0043u, 0x003a0083u, 0x00280005u, 0x00280045u, 0x00280085u, 0x002800c5u, 0x00280105u, 0x00280145u, 0x00280185u,
    0x002801c5u, 0x00280205u, 0x00280245u, 0x00280285u, 0x002802c5u, 0x00280305u, 0x00280345u, 0x00280008u, 0x00280048u, 0x00280088u, 0x002800c8u, 0x00280108u,
    0x00280148u, 0x00280188u, 0x002801c8u, 0x00280208u, 0x00280248u, 0x00280288u, 0x002802c8u, 0x00280308u, 0x00280348u, 0x00280388u, 0x002803c8u, 0x00280408u,
    0x00280448u, 0x00280488u, 0x002804c8u, 0x00280508u, 0x00280548u, 0x00280588u, 0x002805c8u, 0x00280608u, 0x00280648u, 0x00280688u, 0x002806c8u, 0x00280708u,
    0x00280748u, 0x00280788u, 0x002807c8u, 0x006e0007u, 0x006e0047u, 0x003a0087u, 0x00280002u, 0x00280042u, 0x00280082u, 0x002800c2u, 0x00280102u, 0x00280142u,
    0x00280182u, 0x002801c2u, 0x00280202u, 0x00280242u, 0x00280282u, 0x002802c2u, 0x00280302u, 0x00280342u, 0x00280382u, 0x002803c2u, 0x00280009u, 0x00280049u,
    0x00280089u, 0x002800c9u, 0x00280109u, 0x00280149u, 0x00280189u, 0x002801c9u, 0x00280209u, 0x00280249u, 0x00280289u, 0x002802c9u, 0x00280309u, 0x00280349u,
    0x0028000cu, 0x0028004cu, 0x0028008cu, 0x002800ccu, 0x0028010cu, 0x0028014cu, 0x0028018cu, 0x002801ccu, 0x0028020cu, 0x0028024cu, 0x0028028cu, 0x002802ccu,
    0x0028030cu, 0x0028034cu, 0x0028038cu, 0x002803ccu, 0x0028040cu, 0x0028044cu, 0x0028048cu, 0x002804ccu, 0x0028050cu, 0x0028054cu, 0x0028058cu, 0x002805ccu,
    0x0028060cu, 0x0028064cu, 0x0028068cu, 0x002806ccu, 0x0028070cu, 0x0028074cu, 0x0028078cu, 0x002807ccu, 0x02800003u, 0x02800043u, 0x04800083u, 0x04810003u,
    0x04810043u, 0x006e000bu, 0x006e004bu, 0x003a008bu, 0x00280006u, 0x00280046u, 0x00280086u, 0x002800c6u, 0x00280106u, 0x00280146u, 0x00280186u, 0x002801c6u,
    0x00280206u, 0x00280246u, 0x00280286u, 0x002802c6u, 0x00280306u, 0x00280346u, 0x00280386u, 0x002803c6u, 0x0028000du, 0x0028004du, 0x0028008du, 0x002800cdu,
    0x0028010du, 0x0028014du, 0x0028018du, 0x002801cdu, 0x0028020du, 0x0028024du, 0x0028028du, 0x002802cdu, 0x0028030du, 0x0028034du, 0x00280010u, 0x00280050u,
    0x00280090u, 0x002800d0u, 0x00280110u, 0x00280150u, 0x00280190u, 0x002801d0u, 0x00280210u, 0x00280250u, 0x00280290u, 0x002802d0u, 0x00280310u, 0x00280350u,
    0x00280390u, 0x002803d0u, 0x00280410u, 0x00280450u, 0x00280490u, 0x002804d0u, 0x00280510u, 0x00280550u, 0x00280590u, 0x002805d0u, 0x00280610u, 0x00280650u,
    0x00280690u, 0x002806d0u, 0x00280710u, 0x00280750u, 0x00280790u, 0x002807d0u, 0x02800007u, 0x02800047u, 0x04800087u, 0x04810007u, 0x04810047u, 0x006e000fu,
    0x006e004fu, 0x003a008fu, 0x0028000au, 0x0028004au, 0x0028008au, 0x002800cau, 0x0028010au, 0x0028014au, 0x0028018au, 0x002801cau, 0x0028020au, 0x0028024au,
    0x0028028au, 0x002802cau, 0x0028030au, 0x0028034au, 0x0028038au, 0x002803cau, 0x46200003u, 0x46200043u, 0x46200083u, 0x462000c3u, 0x48200103u, 0x00280011u,
    0x00280051u, 0x00280091u, 0x002800d1u, 0x00280111u, 0x00280151u, 0x00280191u, 0x002801d1u, 0x00280211u, 0x00280251u, 0x00280291u, 0x002802d1u, 0x00280311u,
    0x00280351u, 0x00280014u, 0x00280054u, 0x00280094u, 0x002800d4u, 0x00280114u, 0x00280154u, 0x00280194u, 0x002801d4u, 0x00280214u, 0x00280254u, 0x00280294u,
    0x002802d4u, 0x00280314u, 0x00280354u, 0x00280394u, 0x002803d4u, 0x00280414u, 0x00280454u, 0x00280494u, 0x002804d4u, 0x00280514u, 0x00280554u, 0x00280594u,
    0x002805d4u, 0x00280614u, 0x00280654u, 0x00280694u, 0x002806d4u, 0x00280714u, 0x00280754u, 0x00280794u, 0x002807d4u, 0x0280000bu, 0x0280004bu, 0x0480008bu,
    0x0481000bu, 0x0481004bu, 0x006e0013u, 0x006e0053u, 0x003a0093u, 0x0028000eu, 0x0028004eu, 0x0028008eu, 0x002800ceu, 0x0028010eu, 0x0028014eu, 0x0028018eu,
    0x002801ceu, 0x0028020eu, 0x0028024eu, 0x0028028eu, 0x002802ceu, 0x0028030eu, 0x0028034eu, 0x0028038eu, 0x002803ceu, 0x46200007u, 0x46200047u, 0x46200087u,
    0x462000c7u, 0x48200107u, 0x00280015u, 0x00280055u, 0x00280095u, 0x002800d5u, 0x00280115u, 0x00280155u, 0x00280195u, 0x002801d5u, 0x00280215u, 0x00280255u,
    0x00280295u, 0x002802d5u, 0x00280315u, 0x00280355u, 0x00280018u, 0x00280058u, 0x00280098u, 0x002800d8u, 0x00280118u, 0x00280158u, 0x00280198u, 0x002801d8u,
    0x00280218u, 0x00280258u, 0x00280298u, 0x002802d8u, 0x00280318u, 0x00280358u, 0x00280398u, 0x002803d8u, 0x00280418u, 0x00280458u, 0x00280498u, 0x002804d8u,
    0x00280518u, 0x00280558u, 0x00280598u, 0x002805d8u, 0x00280618u, 0x00280658u, 0x00280698u, 0x002806d8u, 0x00280718u, 0x00280758u, 0x00280798u, 0x002807d8u,
    0x0280000fu, 0x0280004fu, 0x0480008fu, 0x0481000fu, 0x0481004fu, 0x006e0017u, 0x006e0057u, 0x003a0097u, 0x00280012u, 0x00280052u, 0x00280092u, 0x002800d2u,
    0x00280112u, 0x00280152u, 0x00280192u, 0x002801d2u, 0x00280212u, 0x00280252u, 0x00280292u, 0x002802d2u, 0x00280312u, 0x00280352u, 0x00280392u, 0x002803d2u,
    0x4620000bu, 0x4620004bu, 0x4620008bu, 0x462000cbu, 0x4820010bu, 0x00280019u, 0x00280059u, 0x00280099u, 0x002800d9u, 0x00280119u, 0x00280159u, 0x00280199u,
    0x002801d9u, 0x00280219u, 0x00280259u, 0x00280299u, 0x002802d9u, 0x00280319u, 0x00280359u, 0x0028001cu, 0x0028005cu, 0x0028009cu, 0x002800dcu, 0x0028011cu,
    0x0028015cu, 0x0028019cu, 0x002801dcu, 0x0028021cu, 0x0028025cu, 0x0028029cu, 0x002802dcu, 0x0028031cu, 0x0028035cu, 0x0028039cu, 0x002803dcu, 0x0028041cu,
    0x0028045cu, 0x0028049cu, 0x002804dcu, 0x0028051cu, 0x0028055cu, 0x0028059cu, 0x002805dcu, 0x0028061cu, 0x0028065cu, 0x0028069cu, 0x002806dcu, 0x0028071cu,
    0x0028075cu, 0x0028079cu, 0x002807dcu, 0x02800013u, 0x02800053u, 0x04800093u, 0x04810013u, 0x04810053u, 0x006e001bu, 0x006e005bu, 0x003a009bu, 0x00280016u,
    0x00280056u, 0x00280096u, 0x002800d6u, 0x00280116u, 0x00280156u, 0x00280196u, 0x002801d6u, 0x00280216u, 0x00280256u, 0x00280296u, 0x002802d6u, 0x00280316u,
    0x00280356u, 0x00280396u, 0x002803d6u, 0x4620000fu, 0x4620004fu, 0x4620008fu, 0x462000cfu, 0x4820010fu, 0x0028001du, 0x0028005du, 0x0028009du, 0x002800ddu,
    0x0028011du, 0x0028015du, 0x0028019du, 0x002801ddu, 0x0028021du, 0x0028025du, 0x0028029du, 0x002802ddu, 0x0028031du, 0x0028035du, 0x02800017u, 0x02800057u,
    0x04800097u, 0x04810017u, 0x04810057u, 0x006e001fu, 0x006e005fu, 0x003a009fu, 0x0028001au, 0x0028005au, 0x0028009au, 0x002800dau, 0x0028011au, 0x0028015au,
    0x0028019au, 0x002801dau, 0x0028021au, 0x0028025au, 0x0028029au, 0x002802dau, 0x0028031au, 0x0028035au, 0x0028039au, 0x002803dau, 0x46200013u, 0x46200053u,
    0x46200093u, 0x462000d3u, 0x48200113u, 0x0240001bu, 0x0240005bu, 0x0440009bu, 0x0440801bu, 0x0440805bu, 0x0641001bu, 0x0641005bu, 0x0841009bu, 0x0841801bu,
    0x0841805bu, 0x0028001eu, 0x0028005eu, 0x0028009eu, 0x002800deu, 0x0028011eu, 0x0028015eu, 0x0028019eu, 0x002801deu, 0x0028021eu, 0x0028025eu, 0x0028029eu,
    0x002802deu, 0x0028031eu, 0x0028035eu, 0x0028039eu, 0x002803deu, 0x46200017u, 0x46200057u, 0x46200097u, 0x462000d7u, 0x48200117u, 0x0210001fu, 0x0210005fu,
    0x0410009fu, 0x0410201fu, 0x0410205fu, 0x0610401fu, 0x0610405fu, 0x0810409fu, 0x0810601fu, 0x0810605fu, 0x0a10801fu, 0x0a10805fu, 0x0c10809fu, 0x0c10a01fu,
    0x0c10a05fu, 0x0e10c01fu, 0x0e10c05fu, 0x1010c09fu, 0x1010e01fu, 0x1010e05fu, 0x1211001fu, 0x1211005fu, 0x1411009fu, 0x1411201fu, 0x1411205fu, 0x1611401fu,
    0x1611405fu, 0x1811409fu, 0x1811601fu, 0x1811605fu, 0x1a11801fu, 0x1a11805fu, 0x1c11809fu, 0x1c11a01fu, 0x1c11a05fu, 0x1e11c01fu, 0x1e11c05fu, 0x2011c09fu,
    0x2011e01fu, 0x2011e05fu, 0x4a10001bu, 0x4a10005bu, 0x4a10009bu, 0x4a1000dbu, 0x4c10011bu, 0x4a10801bu, 0x4a10805bu, 0x4a10809bu, 0x4a1080dbu, 0x4c10811bu,
    0x6204001fu, 0x6204005fu, 0x6204009fu, 0x620400dfu, 0x6404011fu, 0x6204201fu, 0x6204205fu, 0x6204209fu, 0x620420dfu, 0x6404211fu, 0x6204401fu, 0x6204405fu,
    0x6204409fu, 0x620440dfu, 0x6404411fu, 0x6204601fu, 0x6204605fu, 0x6204609fu, 0x620460dfu, 0x6404611fu, 0x6204801fu, 0x6204805fu, 0x6204809fu, 0x620480dfu,
    0x6404811fu, 0x6204a01fu, 0x6204a05fu, 0x6204a09fu, 0x6204a0dfu, 0x6404a11fu, 0x6204c01fu, 0x6204c05fu, 0x6204c09fu, 0x6204c0dfu, 0x6404c11fu, 0x6204e01fu,
    0x6204e05fu, 0x6204e09fu, 0x6204e0dfu, 0x6404e11fu,
};

constexpr int NVB = 6, NR = 4, SW0 = 5, SW1 = 10, NA0 = 4, NA1 = 6, RC = 6, OSEQ = 0, OHEAD = 2, VHEAD = 2, RM = 216, RH = 72, DUR1 = 2450, DUR2 = 600, M1 = 100, M2 = 100, SLEW = 40, NSB = 24, OPF = 0, RELFLAG = 0, PREF = 0, JOIN = 1, NOCHAIN = 0, KVONLY = 0;
constexpr int S_WV = 0, S_WO = 81920;
constexpr int S_MEMT = 163840, S_KX = S_MEMT, S_VX = S_KX + 4096;
constexpr int S_EXP = S_VX + 8192;
constexpr int S_XQK = S_EXP + 2048;
constexpr int S_XVL = S_XQK + 4096;
constexpr int S_XVR = S_XVL + 2048;
constexpr int S_SLOC = S_XVR + 1024;
constexpr int S_SREM = S_SLOC + 1536;
constexpr int S_OT = S_SREM + 1280;
constexpr int S_SUM = S_OT + 2048;
constexpr int ZBYTES = 2048, S_ZERO = S_SUM + 128;
constexpr int S_BK = S_ZERO + ZBYTES;
static_assert(S_BK + 2048 * (SW0 + SW1) <= 231424, "chain smem");
constexpr int G_STAGE = 49152, G_NST = 4, G_EPI = G_STAGE * G_NST;
constexpr int S_BAR = 231424;
constexpr int S_PROF = S_BAR + 256;
constexpr int S_TOTAL = S_PROF + 768;
constexpr int MB_W0 = 0, MB_W1 = 8, MB_S = 16, MB_V = 24, MB_KX = 32;
constexpr int MB_FULL = 64, MB_EMPTY = 96, TQN = 3, MB_TFULL = 128, MB_TEMPTY = 152, S_TQ = 176, MB_SFULL = 208, MB_SEMPTY = 224;
constexpr int NB_MEM = 1  , NB_QK = 3, NB_SL = 4, NB_W3 = 5, NB_O = 6, NB_EXP = 7, NB_MAIN = 8, NB_WG = 9  , NB_TRIG = 11, NB_H2 = 12;

#define TS(i)
#define TV(i, v)
#define ST(i)

template<int REPS> DEVI int probe_near(unsigned char* page0, uint32_t sscratch) {
    uint32_t best0 = 1u << 30, best1 = 1u << 30;
    #pragma unroll 1
    for (int rep = 0; rep < REPS; rep++) {
        uint32_t v, t0, t1, t2;
        t0 = clk();
        asm volatile("atom.relaxed.gpu.global.exch.b32 %0, [%1], %2;" : "=r"(v) : "l"(page0), "r"(0) : "memory");
        asm volatile("st.volatile.shared.u32 [%0], %1;" :: "r"(sscratch), "r"(v) : "memory");
        t1 = clk();
        asm volatile("atom.relaxed.gpu.global.exch.b32 %0, [%1], %2;" : "=r"(v) : "l"(page0 + 4096), "r"(0) : "memory");
        asm volatile("st.volatile.shared.u32 [%0], %1;" :: "r"(sscratch), "r"(v) : "memory");
        t2 = clk();
        best0 = min(best0, t1 - t0); best1 = min(best1, t2 - t1);
    }
    return best1 < best0;
}

DEVI void bar_arrive_if(int id, int n, bool c) { asm volatile("{ .reg .pred q; setp.ne.u32 q, %2, 0; @q bar.arrive %0, %1; }" :: "r"(id), "r"(n), "r"((uint32_t)c) : "memory"); }
DEVI uint32_t clkv() { unsigned long long c; asm volatile("mov.u64 %0, %%clock64;" : "=l"(c) :: "memory"); return (uint32_t)c; }
DEVI void wait_until(uint32_t target) { while ((int)(clkv() - target) < 0) {} __syncwarp(); }
DEVI uint32_t gtl() { unsigned long long t; asm volatile("mov.u64 %0, %%globaltimer;" : "=l"(t) :: "memory"); return (uint32_t)t; }
DEVI void wait_ns(uint32_t T) {
    const uint32_t e = T & ~31u, rest = ((T & 31u) * 7u) >> 2;
    if ((int)(gtl() - e) < 0) { while ((int)(gtl() - e) < 0) {} const uint32_t c = clkv() + rest; while ((int)(clkv() + 12 - c) < 0) {} }
    __syncwarp();
}
DEVI int ldz(uint32_t sb) { int v; asm volatile("ld.volatile.shared.u32 %0, [%1];" : "=r"(v) : "r"(sb + S_ZERO) : "memory"); return v; }
DEVI uint32_t clk_after_bar(uint32_t sb) { const int v = ldz(sb); asm volatile("st.volatile.shared.u32 [%0], %1;" :: "r"(sb + S_SUM + 96), "r"(v) : "memory"); return clkv(); }
DEVI void sched_fence() { asm volatile("pmevent 0;" ::: "memory"); }

DEVI void chain_kv_ready(int seg, int h) { if ((seg & 3) == 0) { int it = 0; while (ld_acq32(&g_sync.kv[((seg >> 2) * 32 + h) * 8]) < 2) spin_guard(it); } }
DEVI void chain_kv_load(const Maps& mp, uint32_t sb, int seg, int h, int j) {
    const uint32_t bar = sb + S_BAR + MB_KX;
    fence_async_glb();
    mbar_expect_tx(bar, 12288);
    tma2d(sb + S_KX, &mp.kvC, h * 128 + j * 64, seg * SEGROWS + 8, bar);
    tma2d(sb + S_VX, &mp.kvC, HD + h * 128 + j * 64, seg * SEGROWS + 8, bar);
    tma2d(sb + S_VX + 4096, &mp.kvC, HD + h * 128 + (j ^ 1) * 64, seg * SEGROWS + 8, bar);
}

DEVI void chain_kv_prefetch(const Maps& mp, int seg, int h, int j) { tma_pf2d(&mp.kvC, h * 128 + j * 64, seg * SEGROWS + 8); tma_pf2d(&mp.kvC, HD + h * 128 + j * 64, seg * SEGROWS + 8); }

__host__ __device__ constexpr int pre_slot(int f, int np, int n) {
    const int hd = n == 20 ? VHEAD : (OHEAD < np && !OSEQ ? OHEAD : np);
    if (np >= n) return f;
    if (f < hd) return f;
    for (int q = hd; q < np; q++) if (f == hd + ((2 * (q - hd) + 1) * (n - hd)) / (2 * (np - hd))) return q;
    return -1;
}
__host__ __device__ constexpr uint32_t xoff_i(int i) { return i == 0 ? 0u : i == 1 ? 0x40000u : i == 2 ? 0x100000u : i == 3 ? 0x140000u : 0x30000u; }
constexpr uint32_t XOFF_HALF = 0x82000u, XREG = 0x200000u;

DEVI void chain_fetch(uint4& a, uint4& b, const unsigned char* src) { a = ld_rlx128(src); b = ld_rlx128(src + 1024); }
DEVI float slew(float cur, float meas) { return cur + fminf(fmaxf(meas - cur, -SLEW), SLEW); }

#define OADDR(f) (WL + S_WO + (T0 + (OSEQ ? (f) / 8 : (f) % NT)) * 16384 + (OSEQ ? (f) % 8 : (f) / NT) * 2048)
template<int KH, bool MEMT>
DEVI void chain_main(const Maps& mp, const uint32_t sb, const int warp, const int lane_, const int h, const int j, unsigned char* __restrict__ xb, const int maj) {
    constexpr int NT = KH ? 3 : 2, T0 = KH ? 0 : 3, NF = NT * 8;
    constexpr int SW = KH ? SW1 : SW0;
    constexpr int NP = NR + SW;
    constexpr int NA = KH ? NA1 : NA0;
    const int p = warp & 3;
    const int lane = opaque(lane_);
    const int mi = lane >> 3, r8 = lane & 7;
    const uint32_t WL = opaque(sb + (((mi >> 1) * 8 + r8) * 128) + (((2 * p + (mi & 1)) ^ r8) << 4));
    const uint32_t L16 = sb + lane * 16;
    const uint32_t BK = L16 + S_BK + (KH ? SW0 * 2048 : 0) + p * 512;
    uint32_t mb_off, rd_off, pub_off, fl_off;
    const int cta = 2 * h + j;
    const bool two = cta < 16;
    const int job = cta + (warp == 1 ? 64 : 0);
    const bool reducer = KH == 0 && (warp == 0 || (warp == 1 && two));
    {
        const int T = (job >> 1) % 40, jr = (T / 20) * 4 + (T & 3), ji = (T % 20) >> 2;
        int it = 0; uint32_t v, u, z;
        do { v = ld_rlx32(&g_sync.side[4 * j + p]); u = ld_rlx32(&g_sync.side[jr]); z = ld_rlx32(&g_sync.side[8]); spin_guard(it); } while (v == 0 || u == 0 || z == 0);
        v ^= maj; u ^= maj; z ^= maj;
        mb_off = uni((4 * j + p) * XREG + (v & 1) * 4096 + h * 128);
        rd_off = uni(jr * XREG + (u & 1) * 4096 + xoff_i(ji) + (job & 1) * XOFF_HALF);
        pub_off = uni(8 * XREG + (z & 1) * 4096 + xoff_i(job / 20) + (job % 20) * 128);
        fl_off = uni(8 * XREG + (z & 1) * 4096 + xoff_i(4) + (h & 3) * 16384);
    }
    uint32_t wq[20][4], wk[20][4];
    if (warp == 0 && lane == 0) { ST(6); }
    mbar_wait(sb + S_BAR + MB_W0, 0);
    if (warp == 0 && lane == 0) { ST(7); }
    #pragma unroll
    for (int ks = 0; ks < 20; ks++) { ldsm4t(wq[ks], WL + S_WV + (KH * 20 + ks) * 2048); ldsm4t(wk[ks], WL + S_WO + (KH * 20 + ks) * 2048); }
    #pragma unroll
    for (int f = 0; f < SW; f++) sts128u(BK + f * 2048, make_uint4(wk[f][0], wk[f][1], wk[f][2], wk[f][3]));
    bar_sync(NB_MAIN, 384);
    if (warp == 0 && lane == 0) { ST(8); }
    mbar_wait(sb + S_BAR + MB_W1, 0);
    if (warp == 0 && lane == 0) { ST(9); }
    const uint32_t pd = mapa(sb, j ^ 1) - sb;
    const uint32_t XW = opaque(sb + S_XQK + (mi >> 1) * 2048 + p * 512 + (mi & 1) * 256 + KH * 128 + r8 * 16);
    uint32_t vb[NVB][4];
    #pragma unroll
    for (int f = 0; f < 20; f++) if (pre_slot(f, NVB, 20) >= 0) ldsm4t(vb[pre_slot(f, NVB, 20)], WL + S_WV + (KH * 20 + f) * 2048);
    for (int s = 0; s < NSEG; s++) {
        float aq[4] = {0, 0, 0, 0}, ak[4] = {0, 0, 0, 0}, av[4] = {0, 0, 0, 0};
        bar_sync(NB_MEM + KH, 192);
        #pragma unroll
        for (int kk = 0; kk < 10; kk++) {
            uint32_t b[4];
            ldsm4t(b, L16 + S_MEMT + KH * 5120 + kk * 512);
            if (kk == 0) TS(0);
            #pragma unroll
            for (int u = 0; u < 2; u++) {
                const int ks = 2 * kk + u;
                if (pre_slot(ks, NVB, 20) >= 0) mma16816(av, vb[pre_slot(ks, NVB, 20)], b[2 * u], b[2 * u + 1]);
                else { uint32_t a[4]; ldsm4t(a, WL + S_WV + (KH * 20 + ks) * 2048); mma16816(av, a, b[2 * u], b[2 * u + 1]); }
                mma16816(aq, wq[ks], b[2 * u], b[2 * u + 1]);
                mma16816(ak, wk[ks], b[2 * u], b[2 * u + 1]);
            }
        }
        sts64u(L16 + p * 512 + S_XVL + KH * 8, pack2(av[0], av[1]), pack2(av[2], av[3]));
        stsm4(XW, pack2(aq[0], aq[1]), pack2(aq[2], aq[3]), pack2(ak[0], ak[1]), pack2(ak[2], ak[3]));
        TS(1);
        if (!MEMT) {
            if (KH == 0 && warp == 3) {
                bar_sync(NB_QK, 384);
                if (lane == 0 && s + 1 < NSEG - 1) chain_kv_load(mp, sb, s + 1, h, j);
                __syncwarp();
            } else bar_arrive(NB_QK, 384);
        }
        if (MEMT) {
            bar_sync(NB_QK, 384);
            uint32_t qa[4][4], kb[4][4];
            #pragma unroll
            for (int c = 0; c < 4; c++) { ldsm4t(kb[c], L16 + S_XQK + 2048 + c * 512); ldsm4t(qa[c], L16 + S_XQK + c * 512); }
            float sa[2][4] = {{0, 0, 0, 0}, {0, 0, 0, 0}};
            #pragma unroll
            for (int c = 0; c < 4; c++) mma16816(sa[c & 1], qa[c], hadd2(kb[c][0], kb[c][1]), hadd2(kb[c][2], kb[c][3]));
            const float y0 = (sa[0][0] + sa[0][2]) + (sa[1][0] + sa[1][2]), y1 = (sa[0][1] + sa[0][3]) + (sa[1][1] + sa[1][3]);
            st_async64(sb + lane * 8 + pd + S_SREM + 1024, __float_as_uint(y0), __float_as_uint(y1), sb + pd + S_BAR + MB_S);
            sts64(L16 + S_SLOC + 1024, y0, y1);
            TS(2);
        }
        uint4 fa = make_uint4(0, 0, 0, 0), fb = fa;
        const int lz = lane + ldz(sb);
        if (KH == 0 && warp == 2) chain_fetch(fa, fb, xb + fl_off + lz * 32);
        uint32_t ws[NP][4];
        bar_sync(NB_SL, 384);
        if (s == NSEG - 1) break;
        #pragma unroll
        for (int f = 0; f < NF; f++) if (pre_slot(f, NP, NF) >= 0 && pre_slot(f, NP, NF) < NA) ldsm4t(ws[pre_slot(f, NP, NF)], OADDR(f));
        if (KH == 0 && warp == 2) {
            int it = 0;
            while (!__all_sync(0xffffffffu, fa.x > (uint32_t)s && fb.x > (uint32_t)s)) { chain_fetch(fa, fb, xb + fl_off + lz * 32); spin_guard(it); }
            const uint32_t base = gtl();
            const int dn = __reduce_max_sync(0xffffffffu, max((int)(fa.y - base), (int)(fb.y - base)));
            const uint32_t rn = __reduce_max_sync(0xffffffffu, max(fa.z, fb.z));
            if (lane == 0) sts64u(sb + S_SUM + 64, base + dn, base + dn + rn);
        }
        __syncwarp();
        bar_sync(NB_W3, 384);
        #pragma unroll
        for (int f = 0; f < NF; f++) if (pre_slot(f, NP, NF) >= NA) ldsm4t(ws[pre_slot(f, NP, NF)], OADDR(f));
        unsigned char* xs = xb + (s & 3) * 16384;
        unsigned char* xo = xs + mb_off + lz * 4;
        sched_fence();
        bar_sync(NB_O, 384);
        uint32_t b[4][4];
        #pragma unroll
        for (int kk = 0; kk < 4; kk++) ldsm4t(b[kk], L16 + S_OT + kk * 512);
        const float2 sm = lds64(sb + S_SUM + (lz & 3) * 8);
        const float i0 = rcpf(sm.x), i1 = rcpf(sm.y);
        if (OSEQ) {
            #pragma unroll
            for (int i = 0; i < NT; i++) {
                float c[2][4] = {{0, 0, 0, 0}, {0, 0, 0, 0}};
                #pragma unroll
                for (int ks = 0; ks < 8; ks++) {
                    const int f = i * 8 + ks;
                    mma16816(c[ks & 1], ws[f % NP], b[ks >> 1][2 * (ks & 1)], b[ks >> 1][2 * (ks & 1) + 1]);
                    if (f + NP < NF) ldsm4t(ws[f % NP], OADDR(f + NP));
                    if (f == 0) TS(3);
                    if (OSEQ == 2 && ks == 3) sched_fence();
                }
                st_rlx32(xo + xoff_i(T0 + i), nz(pack2((c[0][0] + c[1][0]) * i0, (c[0][1] + c[1][1]) * i1)));
                st_rlx32(xo + xoff_i(T0 + i) + XOFF_HALF, nz(pack2((c[0][2] + c[1][2]) * i0, (c[0][3] + c[1][3]) * i1)));
                if (i + 1 < NT) sched_fence();
            }
        } else {
            float c[NT][4];
            #pragma unroll
            for (int i = 0; i < NT; i++) { c[i][0] = c[i][1] = c[i][2] = c[i][3] = 0.f; }
            #pragma unroll
            for (int f = 0; f < NF; f++) {
                const int ks = f / NT;
                if (pre_slot(f, NP, NF) >= 0) mma16816(c[f % NT], ws[pre_slot(f, NP, NF)], b[ks >> 1][2 * (ks & 1)], b[ks >> 1][2 * (ks & 1) + 1]);
                else { uint32_t a[4]; ldsm4t(a, OADDR(f)); mma16816(c[f % NT], a, b[ks >> 1][2 * (ks & 1)], b[ks >> 1][2 * (ks & 1) + 1]); }
                if (f == 0) TS(3);
            }
            #pragma unroll
            for (int i = 0; i < NT; i++) {
                st_rlx32(xo + xoff_i(T0 + i), nz(pack2(c[i][0] * i0, c[i][1] * i1)));
                st_rlx32(xo + xoff_i(T0 + i) + XOFF_HALF, nz(pack2(c[i][2] * i0, c[i][3] * i1)));
            }
        }
        TS(4);
        bar_arrive(NB_EXP, 384);
        const uint32_t t1 = lds32u(sb + S_SUM + 64), t2 = lds32u(sb + S_SUM + 68);
        if (reducer) {
            unsigned char* mb = xs + rd_off + lz * 16; unsigned char* pub = xs + pub_off + (lz & 7) * 16 + (lz >> 3) * 4;
            const uint32_t idm = (lz >> 3) != (lz & 3) ? 0u : (lz & 4) ? 0x3F800000u : 0x00003F80u;
            sched_fence();
            wait_ns(t1);
            TS(5);
            int it = 0;
            while (true) {
                const uint32_t cr = clkv();
                uint4 A[8];
                #pragma unroll
                for (int r = 0; r < 8; r++) A[r] = ld_rlx128(mb + r * 512);
                float a[4][4];
                uint32_t mn = 0xffffffffu;
                #pragma unroll
                for (int r = 0; r < 4; r++) { a[r][0] = a[r][1] = a[r][2] = a[r][3] = 0.f; }
                #pragma unroll
                for (int r = 0; r < 8; r++) {
                    mma1688(a[r & 1], A[r].x, A[r].y, idm); mma1688(a[2 + (r & 1)], A[r].z, A[r].w, idm);
                    mn = min(mn, A[r].x);
                }
                const bool ok = __all_sync(0xffffffffu, mn != 0);
                const bool h4 = lz & 16, h3 = lz & 8;
                float k[4];
                #pragma unroll
                for (int i = 0; i < 4; i++) { const float lo = a[0][i] + a[1][i], hi = a[2][i] + a[3][i]; k[i] = (h4 ? hi : lo) + __shfl_xor_sync(0xffffffffu, h4 ? lo : hi, 16); }
                const float y0 = (h3 ? k[2] : k[0]) + __shfl_xor_sync(0xffffffffu, h3 ? k[0] : k[2], 8), y1 = (h3 ? k[3] : k[1]) + __shfl_xor_sync(0xffffffffu, h3 ? k[1] : k[3], 8);
                asm volatile("{ .reg .pred q; setp.ne.u32 q, %2, 0; @q st.relaxed.gpu.global.u32 [%0], %1; }" :: "l"(pub), "r"(nz(pack2(y0, y1))), "r"((uint32_t)ok) : "memory");
                if (ok) { if (lane == 0) sts32u(sb + S_SUM + 80 + warp * 4, clkv() - cr); break; }
                spin_guard(it);
            }
            __syncwarp();
            TS(6); TV(7, it);
        } else {
            wait_ns(t1 + NSB);
        }
        #pragma unroll
        for (int f = 0; f < SW; f++) if (f < RC) { const uint4 v = lds128u(BK + f * 2048); wk[f][0] = v.x; wk[f][1] = v.y; wk[f][2] = v.z; wk[f][3] = v.w; }
        wait_ns(t2 + NSB);
        #pragma unroll
        for (int f = 0; f < 20; f++) if (pre_slot(f, NVB, 20) >= 0) ldsm4t(vb[pre_slot(f, NVB, 20)], WL + S_WV + (KH * 20 + f) * 2048);
        #pragma unroll
        for (int f = RC; f < SW; f++) { const uint4 v = lds128u(BK + f * 2048); wk[f][0] = v.x; wk[f][1] = v.y; wk[f][2] = v.z; wk[f][3] = v.w; }
    }
}

DEVI void chain_export(uint32_t sb, uint32_t L16, int w, int lane, uint32_t vl0, uint32_t vl1) {
    uint32_t kk4[4];
    ldsm4t(kk4, L16 + w * 512 + S_XQK + 2048);
    const uint32_t EA = sb + S_EXP + (lane >> 2) * 128 + (lane & 3) * 4 + (((2 * w) ^ (lane >> 2)) << 4);
    const uint32_t v0 = movm(vl0), v1 = movm(vl1);
    sts32u(EA, hadd2(kk4[0], kk4[1])); sts32u(EA ^ 16, hadd2(kk4[2], kk4[3]));
    sts32u(EA + 1024, v0); sts32u((EA ^ 16) + 1024, v1);
    fence_async_smem();
}
DEVI void chain_export_store(const Maps& mp, uint32_t sb, int h, int j, int s) {
    tma_store2d(&mp.kvE, sb + S_EXP, h * 128 + j * 64, s * SEGROWS); tma_store2d(&mp.kvE, sb + S_EXP + 1024, HD + h * 128 + j * 64, s * SEGROWS); bulk_commit();
}
DEVI void chain_kv_frags(uint32_t (*kx)[4], uint32_t (*va)[4], uint32_t sb, int w, int lane) {
    const int mi = lane >> 3, r8 = lane & 7;
    const uint32_t KX = sb + S_KX + (8 * w + r8) * 128 + ((mi ^ r8) << 4);
    const uint32_t VX = sb + S_VX + (((mi >> 1) * 8 + r8) * 128) + (((2 * w + (mi & 1)) ^ r8) << 4);
    ldsm4(kx[0], KX); ldsm4(kx[1], KX ^ 64);
    #pragma unroll
    for (int q = 0; q < 4; q++) ldsm4t(va[q], VX + q * 2048);
}

DEVI void chain_aux(const Maps& mp, const uint32_t sb, const int warp, const int lane_, const int h, const int j, unsigned char* __restrict__ xb, const bf16* __restrict__ mem0, const int maj) {
    const int w = warp - 8;
    const int lane = opaque(lane_);
    const int cta = 2 * h + j;
    if (w == 0 && lane == 0) {
        ST(5);
        mbar_expect_tx(sb + S_BAR + MB_W0, 2 * 81920);
        for (int i = 0; i < 5; i++) tma2d(sb + S_WO + i * 16384, &mp.wkC, h * 128 + j * 64, i * 128, sb + S_BAR + MB_W0);
        for (int i = 0; i < 5; i++) tma2d(sb + S_WV + i * 16384, &mp.wqC, h * 128 + j * 64, i * 128, sb + S_BAR + MB_W0);
    }
    if (w == 1 && lane == 0) { sts64u(sb + S_SUM + 64, 0, 0); sts128u(sb + S_SUM + 32, make_uint4(__float_as_uint(0.56f), 0, 0, 0)); sts64(sb + S_SUM + 48, (float)DUR1, (float)DUR2); sts64u(sb + S_SUM + 80, 0, 0); }
    for (int i = lane + 32 * w; i < ZBYTES / 16; i += 128) sts128u(sb + S_ZERO + i * 16, make_uint4(0, 0, 0, 0));
    fence_async_smem();
    const uint32_t L16 = sb + lane * 16;
    const uint32_t srow = L16 + S_MEMT + 2560 * w;
    uint32_t bc_off, clr_mb, clr_bc, fl_off;
    {
        const int job = cta + (w == 0 ? 64 : 0), T = (job >> 1) % 40, jr = (T / 20) * 4 + (T & 3), ji = (T % 20) >> 2;
        int it = 0; uint32_t u, z;
        do { u = ld_rlx32(&g_sync.side[jr]); z = ld_rlx32(&g_sync.side[8]); spin_guard(it); } while (u == 0 || z == 0);
        u ^= maj; z ^= maj;
        bc_off = uni(8 * XREG + (z & 1) * 4096 + xoff_i(w));
        clr_mb = uni(jr * XREG + (u & 1) * 4096 + xoff_i(ji) + (job & 1) * XOFF_HALF);
        clr_bc = uni(8 * XREG + (z & 1) * 4096 + xoff_i(job / 20) + (job % 20) * 128);
        fl_off = uni(8 * XREG + (z & 1) * 4096 + xoff_i(4));
    }
    const bool clearer = w == 1 || (w == 0 && cta < 16);
    uint4 m0[5];
    #pragma unroll
    for (int r = 0; r < 5; r++) {
        const unsigned short* mp0 = (const unsigned short*)mem0 + 160 * w + 32 * r + lane;
        m0[r].x = mp0[0] | ((uint32_t)mp0[DM] << 16); m0[r].y = mp0[2 * DM] | ((uint32_t)mp0[3 * DM] << 16);
        m0[r].z = mp0[4 * DM] | ((uint32_t)mp0[5 * DM] << 16); m0[r].w = mp0[6 * DM] | ((uint32_t)mp0[7 * DM] << 16);
    }
    bar_sync(NB_MAIN, 384);
    if (w == 3 && lane == 0) {
        mbar_expect_tx(sb + S_BAR + MB_W1, 2 * 81920);
        for (int i = 0; i < 5; i++) { tma2d(sb + S_WV + i * 16384, &mp.wvC, h * 128 + j * 64, i * 128, sb + S_BAR + MB_W1); tma2d(sb + S_WO + i * 16384, &mp.woC, j * 320 + i * 64, h * 128, sb + S_BAR + MB_W1); }
    }
    if (w == 1 && lane == 0) { chain_kv_ready(0, h); chain_kv_load(mp, sb, 0, h, j); }
    __syncwarp();
    const uint32_t pd = mapa(sb, j ^ 1) - sb;
    const uint32_t OTW = opaque(sb + S_OT + (((j ^ (lane >> 4)) * 64 + w * 16 + (lane & 15)) * 16));
    const uint32_t SW_ = L16 + (w >> 1) * 512 + (w & 1) * 8, L8 = sb + lane * 8;
    uint32_t kx[2][4], va[4][4];
    if (w == 0 && lane == 0) { ST(10); }
    mbar_wait(sb + S_BAR + MB_KX, 0);
    if (w == 0 && lane == 0) { ST(11); }
    chain_kv_frags(kx, va, sb, w, lane);
    bar_sync(NB_MAIN, 128);
    #pragma unroll
    for (int r = 0; r < 5; r++) sts128u(srow + r * 512, m0[r]);
    bar_arrive(NB_MEM + (w >> 1), 192);

    for (int s = 0; s < NSEG; s++) {
        bar_sync(NB_MAIN, 128);
        if (w == 2) {
            const uint32_t cs = clk_after_bar(sb), ga = gtl();
            const uint4 st = lds128u(sb + S_SUM + 32);
            float2 du = lds64(sb + S_SUM + 48);
            const uint32_t ce = lds32u(sb + S_SUM + 72), ra = lds32u(sb + S_SUM + 80), rb = lds32u(sb + S_SUM + 84);
            uint32_t g, c;
            do { g = gtl(); c = clkv(); } while (g == ga);
            float nspc = __uint_as_float(st.x);
            if (s > 0) {
                const float r = __fdividef((float)(g - st.z), (float)(c - st.w)); nspc = s > 1 ? 0.5f * (nspc + r) : r;
                du.x = slew(du.x, (float)(ce - st.y)); du.y = slew(du.y, (float)max(ra, rb));
            }
            const uint32_t a1 = g + (uint32_t)(nspc * (du.x + (float)M1 - (float)(c - cs))), a2 = (uint32_t)(nspc * (du.y + (float)M2));
            st_rlx32(xb + fl_off + (lane >> 3) * 16384 + cta * 32 + (lane & 7) * 4, (lane & 3) == 1 ? a1 : (lane & 3) == 2 ? a2 : (uint32_t)(s + 1));
            __syncwarp();
            if (lane == 0) {
                sts128u(sb + S_SUM + 32, make_uint4(__float_as_uint(nspc), cs, g, c)); sts64(sb + S_SUM + 48, du.x, du.y);
            }
        } else if (lane == 0) {
            if (w == 0) mbar_expect_tx(sb + S_BAR + MB_S, 1280 + 1024);
            if (w == 3 && s > 0) chain_export_store(mp, sb, h, j, s - 1);
            if (clearer && s > 1) { bulk_store(xb + ((s + 2) & 3) * 16384 + clr_mb, sb + S_ZERO, 2048); bulk_store(xb + ((s + 2) & 3) * 16384 + clr_mb + 2048, sb + S_ZERO, 2048); bulk_store(xb + ((s + 2) & 3) * 16384 + clr_bc, sb + S_ZERO, 128); bulk_commit(); }
        }
        __syncwarp();
        bar_sync(NB_QK, 384);
        uint32_t vl0, vl1;
        {
            uint32_t qa[4][4];
            #pragma unroll
            for (int c = 0; c < 4; c++) ldsm4t(qa[c], L16 + S_XQK + c * 512);
            const uint4 vl = lds128u(L16 + w * 512 + S_XVL); vl0 = hadd2(vl.x, vl.z); vl1 = hadd2(vl.y, vl.w);
            float sa[2][4] = {{0, 0, 0, 0}, {0, 0, 0, 0}};
            #pragma unroll
            for (int c = 0; c < 4; c++) mma16816(sa[c & 1], qa[c], kx[c >> 1][2 * (c & 1)], kx[c >> 1][2 * (c & 1) + 1]);
            const float y0 = (sa[0][0] + sa[0][2]) + (sa[1][0] + sa[1][2]), y1 = (sa[0][1] + sa[0][3]) + (sa[1][1] + sa[1][3]);
            st_async64(L8 + w * 256 + pd + S_SREM, __float_as_uint(y0), __float_as_uint(y1), sb + pd + S_BAR + MB_S);
            st_async64(L8 + w * 256 + pd + S_XVR, vl0, vl1, sb + pd + S_BAR + MB_S);
            sts64(SW_ + S_SLOC, y0, y1);
        }
        TS(0);
        bar_sync(NB_SL, 384);
        if (s == NSEG - 1) {
            if (w == 3 && lane == 0) bulk_wait<0>();
            bar_sync(NB_MAIN, 128);
            chain_export(sb, L16, w, lane, vl0, vl1);
            bar_sync(NB_MAIN, 128);
            if (w == 3 && lane == 0) { chain_export_store(mp, sb, h, j, s); bulk_wait<0>(); fence_gpu(); st_rlx32(&g_sync.prog[(h >> 1) * 32 + (h & 1) * 2 + j], NSEG); }
            mbar_wait(sb + S_BAR + MB_S, s & 1);
            if (clearer && lane == 0) { bulk_store(xb + ((s + 3) & 3) * 16384 + clr_mb, sb + S_ZERO, 2048); bulk_store(xb + ((s + 3) & 3) * 16384 + clr_mb + 2048, sb + S_ZERO, 2048); bulk_commit(); bulk_wait<0>(); }
            break;
        }
        const uint4 la = lds128u(L16 + S_SLOC), lb = lds128u(L16 + S_SLOC + 512); const float2 lc = lds64(L16 + S_SLOC + 1024);
        mbar_wait(sb + S_BAR + MB_S, s & 1);
        TS(1);
        const float2 r0 = lds64(L8 + S_SREM), r1 = lds64(L8 + S_SREM + 256), r2 = lds64(L8 + S_SREM + 512), r3 = lds64(L8 + S_SREM + 768), r4 = lds64(L8 + S_SREM + 1024);
        float e[10] = {__uint_as_float(la.x) + r0.x, __uint_as_float(la.y) + r0.y, __uint_as_float(la.z) + r1.x, __uint_as_float(la.w) + r1.y,
                       __uint_as_float(lb.x) + r2.x, __uint_as_float(lb.y) + r2.y, __uint_as_float(lb.z) + r3.x, __uint_as_float(lb.w) + r3.y, lc.x + r4.x, lc.y + r4.y};
        const float csc = 0.08838834764831845f * 1.4426950408889634f;
        const float mt = fmaxf(fmaxf(fmaxf(fmaxf(e[0], e[1]), fmaxf(e[2], e[3])), fmaxf(fmaxf(e[4], e[5]), fmaxf(e[6], e[7]))), fmaxf(e[8], e[9]));
        const float m1 = __shfl_xor_sync(0xffffffffu, mt, 1), m2 = __shfl_xor_sync(0xffffffffu, mt, 2), m3 = __shfl_xor_sync(0xffffffffu, mt, 3);
        const float2 vr = lds64(L8 + w * 256 + S_XVR);
        bar_arrive(NB_W3, 384);
        sched_fence();
        const float mc = mt * csc;
        #pragma unroll
        for (int i = 0; i < 10; i++) e[i] = ex2(fmaf(e[i], csc, -mc));
        const float m = fmaxf(fmaxf(mt, m1), fmaxf(m2, m3));
        const float f = ex2((mt - m) * csc);
        const uint32_t p0 = pack2(e[0] * f, e[1] * f), p1 = pack2(e[2] * f, e[3] * f), p2 = pack2(e[4] * f, e[5] * f), p3 = pack2(e[6] * f, e[7] * f), p4 = pack2(e[8] * f, e[9] * f);
        float o0[4] = {0, 0, 0, 0}, o1[4] = {0, 0, 0, 0}, sm[4] = {0, 0, 0, 0};
        const uint32_t ONE = 0x3F803F80u;
        mma16816(o0, va[0], p0, p1); mma16816(o1, va[2], p0, p1); mma16816(sm, ONE, ONE, ONE, ONE, p0, p1);
        mma16816(o0, va[1], p2, p3); mma16816(o1, va[3], p2, p3); mma16816(sm, ONE, ONE, ONE, ONE, p2, p3);
        mma1688(o0, vl0, vl1, p4); mma1688(o1, __float_as_uint(vr.x), __float_as_uint(vr.y), p4); mma1688(sm, ONE, ONE, p4);
        stsm4(OTW, pack2(o0[0], o0[1]), pack2(o0[2], o0[3]), pack2(o1[0], o1[1]), pack2(o1[2], o1[3]));
        if (lane < 4) sts64(sb + lane * 8 + S_SUM, sm[0], sm[1]);
        bar_arrive(NB_O, 384);
        TS(2);
        if (w == 3 && lane == 0) { bulk_wait<0>(); if ((s & 3) == 0 && s > 0) st_rlx32(&g_sync.prog[(h >> 1) * 32 + (h & 1) * 2 + j], s); }
        if (w == 1 && lane == 0 && s + 2 < NSEG - 1) { chain_kv_ready(s + 2, h); chain_kv_prefetch(mp, s + 2, h, j); }
        __syncwarp();
        unsigned char* bc = xb + (s & 3) * 16384 + bc_off + lane * 16;
        bar_sync(NB_EXP, 384);
        if (w == 2) { const uint32_t ce = clk_after_bar(sb); if (lane == 0) sts32u(sb + S_SUM + 72, ce); }
        const uint32_t t2 = lds32u(sb + S_SUM + 68);
        chain_export(sb, L16, w, lane, vl0, vl1);
        if (s + 1 < NSEG - 1) mbar_wait(sb + S_BAR + MB_KX, (s + 1) & 1);
        chain_kv_frags(kx, va, sb, w, lane);
        bar_sync(NB_MAIN, 128);
        wait_ns(t2);
        TS(6);
        int it = 0;
        while (true) {
            uint4 A[5];
            #pragma unroll
            for (int r = 0; r < 5; r++) A[r] = ld_rlx128(bc + r * 512);
            #pragma unroll
            for (int r = 0; r < 5; r++) sts128u(srow + r * 512, A[r]);
            const bool ok = __all_sync(0xffffffffu, min(min(min(A[0].x, A[1].x), min(A[2].x, A[3].x)), A[4].x) != 0);
            bar_arrive_if(NB_MEM + (w >> 1), 192, ok);
            if (ok) break;
            spin_guard(it);
        }
        TS(7); TV(9, it);
    }
}

struct Task { int type, m, n, k0, nk, split, row; bool share, half; };
DEVI Task decode_task(uint32_t w, int rank) {
    Task t; t.type = w & 3; t.n = (w >> 6) & 31; t.k0 = (w >> 11) & 127; t.nk = (w >> 18) & 127; t.split = (w >> 25) & 31; t.share = true;
    t.half = false; t.row = 0;
    if ((w >> 30) & 1) { t.type = T_RED; t.m = (w >> 2) & 15; return t; }
    const int mp = (w >> 2) & 15;
    t.half = t.type == T_KV && t.split;
    if (t.type != T_OUT) { t.m = t.half ? mp : 2 * mp + rank; t.row = t.m * 128 + (t.half ? rank * 64 : 0); }
    else { t.m = mp; if (t.n < 2) t.n = 2 * t.n + rank; else { t.n = 4; t.share = false; t.k0 += rank * t.nk; t.split += rank; } }
    return t;
}
DEVI uint32_t post_task(uint32_t sb, uint32_t other, int rank, uint32_t idx, uint32_t& tslot, uint32_t& tph) {
    uint32_t task;
    if (rank == 0) {
        task = idx < NTASKS ? c_tasks[idx] : 0xffffffffu;
        mbar_wait(sb + S_BAR + MB_TEMPTY + 8 * tslot, tph ^ 1);
        asm volatile("st.async.weak.shared::cluster.mbarrier::complete_tx::bytes.b32 [%0], %1, [%2];" :: "r"(other + S_BAR + S_TQ + 4 * tslot), "r"(task), "r"(other + S_BAR + MB_TFULL + 8 * tslot) : "memory");
        sts32u(sb + S_BAR + S_TQ + 4 * tslot, task);
        mbar_arrive(sb + S_BAR + MB_TFULL + 8 * tslot);
    } else {
        mbar_expect_tx(sb + S_BAR + MB_TFULL + 8 * tslot, 4);
        mbar_wait(sb + S_BAR + MB_TFULL + 8 * tslot, tph);
        asm volatile("ld.volatile.shared.u32 %0, [%1];" : "=r"(task) : "r"(sb + S_BAR + S_TQ + 4 * tslot) : "memory");
        if (task != 0x7fffffffu) mbar_arrive_rlx(other + S_BAR + MB_TEMPTY + 8 * tslot);
    }
    if (++tslot == TQN) { tslot = 0; tph ^= 1; }
    return task;
}
DEVI void gemm_producer(const Maps& mp, const uint32_t sb, const int rank, const int role) {
    const bool first = role >= 32;
    uint32_t st = 0, ph = 1, tslot = 0, tph = 0;
    const uint32_t other = mapa(sb, rank ^ 1);
    uint32_t next = first ? 65 - role : rank ? 0 : 34 + atomicAdd(g_sync.queue, 1);
    uint32_t ntask = post_task(sb, other, rank, next, tslot, tph);
    if (first) { ST(5); }
    while (true) {
        const uint32_t task = ntask;
        if (task == 0xffffffffu) break;
        const Task t = decode_task(task, rank);
        if (t.type == T_RED) {
            mbar_wait(sb + S_BAR + MB_EMPTY + 8 * st, ph);
            mbar_arrive(sb + S_BAR + MB_FULL + 8 * st);
            mbar_wait(sb + S_BAR + MB_EMPTY + 8 * st, ph ^ 1);
            if (++st == G_NST) { st = 0; ph ^= 1; }
            if (rank == 0) next = 34 + atomicAdd(g_sync.queue, 1);
            ntask = post_task(sb, other, rank, next, tslot, tph);
            continue;
        }
        const int m = t.m, n = t.n, nk = t.nk;
        const int nst = t.type == T_QA ? nk + 4 : nk;
        const CUtensorMap* bm = t.type == T_KV ? (rank ? &mp.wv : &mp.wk) : t.type == T_UP ? (rank ? &mp.wu : &mp.wg) : &mp.wq;
        const int c0 = t.type == T_QA ? n * 256 + rank * 128 : n * 128;
        for (int i = 0; i < nst; i++) {
            if (t.type != T_QA) {
                if (rank == 0 && i == nst - 3) next = 34 + atomicAdd(g_sync.queue, 1);
                if (i == nst - 2 + rank) ntask = post_task(sb, other, rank, next, tslot, tph);
            }
            const uint32_t dst = sb + st * G_STAGE, full = sb + S_BAR + MB_FULL + 8 * st;
            if (t.type == T_OUT) {
                const int kb = t.k0 + i;
                if (kb < 64 ? ((kb & 3) == 0 || i == 0) : (kb == 64 || i == 0)) {
                    for (int r = 0; r < 2; r++) if (!t.share || r == rank) { if (kb < 64) wait_ge(&g_sync.oc[((2 * m + r) * 16 + (kb >> 2)) * 8], 2); else wait_ge(&g_sync.hc[(2 * m + r) * 8], 14 * 2); }
                    fence_async_glb();
                }
                if (OPF && i + OPF < nk && m < 6) { tma_pf2d(&mp.ahL, (kb + OPF) * 64, m * 256 + rank * 128); if (!t.share) tma_pf2d(&mp.ahL, (kb + OPF) * 64, m * 256 + (rank ^ 1) * 128); }
                mbar_wait(sb + S_BAR + MB_EMPTY + 8 * st, ph);
                mbar_expect_tx(full, 49152);
                const CUtensorMap* wm = kb < 64 ? &mp.wo : &mp.wd; const int kr = (kb < 64 ? kb : kb - 64) * 64;
                tma2d(dst, wm, n * 128, kr, full); tma2d(dst + 8192, wm, n * 128 + 64, kr, full);
                if (t.share) tma2d_mc(dst + 16384 + rank * 16384, &mp.ahL, kb * 64, m * 256 + rank * 128, full);
                else { tma2d(dst + 16384, &mp.ahL, kb * 64, m * 256, full); tma2d(dst + 32768, &mp.ahL, kb * 64, m * 256 + 128, full); }
            } else if (i < nk) {
                mbar_wait(sb + S_BAR + MB_EMPTY + 8 * st, ph);
                mbar_expect_tx(full, 49152);
                tma2d_mc(dst + 16384 + rank * 16384, bm, c0, i * 64, full); tma2d_mc(dst + 24576 + rank * 16384, bm, c0 + 64, i * 64, full);
                tma2d(dst, &mp.x, i * 64, t.row, full);
            } else {
                const int e = i - nk;
                if (e == 0) {
                    int it = 0;
                    while (true) {
                        const uint4 pr = ld_rlx128(&g_sync.prog[32 * n]);
                        const uint32_t k0 = ld_rlx32(&g_sync.kv[(m * 32 + 2 * n) * 8]), k1 = ld_rlx32(&g_sync.kv[(m * 32 + 2 * n + 1) * 8]);
                        if ((NOCHAIN || min4(pr) >= (uint32_t)(4 * m + 4)) && min(k0, k1) >= 2) break;
                        spin_guard(it); __nanosleep(50);
                    }
                    asm volatile("fence.acquire.gpu;" ::: "memory");
                    fence_async_glb();
                }
                mbar_wait(sb + S_BAR + MB_EMPTY + 8 * st, ph);
                mbar_expect_tx(full, 40960);
                const int col = (e >> 1) * HD + (2 * n + (e & 1)) * 128;
                tma2d(dst, &mp.kvA, col, m * 160, full); tma2d(dst + 20480, &mp.kvA, col + 64, m * 160, full);
            }
            if (++st == G_NST) { st = 0; ph ^= 1; }
        }
        if (t.type != T_UP) {
            mbar_wait(sb + S_BAR + MB_EMPTY + 8 * st, ph);
            mbar_arrive(sb + S_BAR + MB_FULL + 8 * st);
            if (++st == G_NST) { st = 0; ph ^= 1; }
        }
        if (t.type == T_QA) {
            if (rank == 0) next = 34 + atomicAdd(g_sync.queue, 1);
            ntask = post_task(sb, other, rank, next, tslot, tph);
        }
    }
}

struct Pipe { uint32_t st, ph; };
DEVI void pipe_adv(Pipe& p) { if (++p.st == G_NST) { p.st = 0; p.ph ^= 1; } }
DEVI void release_stage(uint32_t rel, uint32_t st, int lane) { if (lane < 2) mbar_arrive_rlx(rel + 8 * st); }

template<bool OUTT, bool FIRST>
DEVI void issue_block(float* acc, uint32_t base, int wg) {
    const uint64_t da = mkdesc(base + wg * 8192, 8192, 1024), db = mkdesc(base + 16384, 8192, 1024);
    wg_fence();
    #pragma unroll
    for (int k = 0; k < 4; k++) {
        if (FIRST && k == 0) { if (OUTT) wg_ss256_z<1, 0>(acc, da, db); else wg_ss256_z<0, 1>(acc, da, db); }
        else if (OUTT) wg_ss256<1, 0>(acc, da + k * 128, db + k * 2, 1);
        else wg_ss256<0, 1>(acc, da + k * 2, db + k * 128, 1);
    }
    wg_commit();
}
template<bool OUTT>
DEVI void gemm_mainloop(float* acc, const uint32_t sb, Pipe& pp, const int nk, const int wg, const int lane, const uint32_t rel) {
    mbar_wait(sb + S_BAR + MB_FULL + 8 * pp.st, pp.ph);
    issue_block<OUTT, true>(acc, sb + pp.st * G_STAGE, wg);
    uint32_t prev = pp.st; pipe_adv(pp);
    #pragma unroll 1
    for (int i = 1; i < nk; i++) {
        mbar_wait(sb + S_BAR + MB_FULL + 8 * pp.st, pp.ph);
        issue_block<OUTT, false>(acc, sb + pp.st * G_STAGE, wg);
        wg_wait<1>(); release_stage(rel, prev, lane);
        prev = pp.st; pipe_adv(pp);
    }
    wg_wait<0>(); release_stage(rel, prev, lane);
}

enum { E_ROWS = 0, E_TRANS = 1, E_RAW = 2 };
template<int MODE, int NB>
DEVI void dump_tile(const uint32_t* pk, const uint32_t sb, Pipe& pp, uint32_t& sph, int wg, int wi, int lane) {
    const int mi = lane >> 3, r8 = lane & 7;
    mbar_wait(sb + S_BAR + MB_SEMPTY + 8 * wg, sph ^ 1);
    #pragma unroll
    for (int B = 0; B < NB; B++) {
        if (B == 2) mbar_wait(sb + S_BAR + MB_FULL + 8 * pp.st, pp.ph);
        const uint32_t stg = sb + (B < 2 ? G_EPI : pp.st * G_STAGE) + wg * 16384 + (B & 1) * 8192;
        const uint32_t* v = pk + 16 * B;
        #pragma unroll
        for (int c = 0; c < 4; c++) {
            if (MODE == E_ROWS) stsm4(stg + (wi * 16 + (mi & 1) * 8 + r8) * 128 + (((2 * c + (mi >> 1)) ^ r8) << 4), v[4 * c], v[4 * c + 1], v[4 * c + 2], v[4 * c + 3]);
            else sts128u(stg + wi * 2048 + c * 512 + lane * 16, make_uint4(v[4 * c], v[4 * c + 1], v[4 * c + 2], v[4 * c + 3]));
        }
    }
    if (NB > 2) pipe_adv(pp);
    fence_async_smem();
    __syncwarp();
    if (lane == 0) mbar_arrive(sb + S_BAR + MB_SFULL + 8 * wg);
    sph ^= 1;
}
DEVI uint32_t next_task(uint32_t sb, uint32_t tem0, uint32_t& tslot, uint32_t& tph, bool arrive) {
    mbar_wait(sb + S_BAR + MB_TFULL + 8 * tslot, tph);
    uint32_t task; asm volatile("ld.volatile.shared.u32 %0, [%1];" : "=r"(task) : "r"(sb + S_BAR + S_TQ + 4 * tslot) : "memory");
    task = uni(task);
    if (arrive) mbar_arrive_rlx(tem0 + 8 * tslot);
    if (++tslot == TQN) { tslot = 0; tph ^= 1; }
    return task;
}
DEVI void gemm_storer(const Maps& mp, const uint32_t sb, const int wg, const int lane, const int rank) {
    const uint32_t tem0 = mapa(sb + S_BAR + MB_TEMPTY, 0), em0 = mapa(sb + S_BAR + MB_EMPTY, 0), em1 = mapa(sb + S_BAR + MB_EMPTY, 1);
    uint32_t tslot = 0, tph = 0, sph = 0, st = 0;
    while (true) {
        const uint32_t task = next_task(sb, tem0, tslot, tph, lane == 0);
        if (task == 0xffffffffu) break;
        const Task t = decode_task(task, rank);
        if (t.type == T_RED) { st = (st + 1) % G_NST; continue; }
        st = (st + t.nk + (t.type == T_QA ? 4 : 0)) % G_NST;
        if (t.half && wg) { st = (st + 1) % G_NST; continue; }
        if (lane == 0) {
            mbar_wait(sb + S_BAR + MB_SFULL + 8 * wg, sph);
            const int nb = t.type == T_UP ? 2 : 4, row = t.row + wg * 64;
            uint32_t* flag = nullptr;
            for (int B = nb - 1; B >= 0; B--) {
                if (B == 1) bulk_commit();
                const uint32_t stg = sb + (B < 2 ? G_EPI : st * G_STAGE) + wg * 16384 + (B & 1) * 8192;
                if (t.type == T_KV) {
                    const int col = (B >> 1) * HD + t.n * 128 + (B & 1) * 64, r = (row >> 5) * SEGROWS + 8;
                    tma_store2d(&mp.kvC, stg, col, r); tma_store2d(&mp.kvC, stg + 4096, col, r + SEGROWS);
                } else if (t.type == T_UP) tma_store2d(&mp.ahS, stg, HD + t.n * 128 + B * 64, row);
                else if (t.type == T_QA) tma_store2d(&mp.ahS, stg, t.n * 256 + B * 64, row);
                else bulk_store((unsigned char*)g_part + ((size_t)(part_slot(t.m, t.n) + t.split) * 8 + wg * 4 + B) * 8192, stg, 8192);
            }
            bulk_commit();
            if (t.type == T_KV) flag = &g_sync.kv[(t.m * 32 + t.n) * 8]; else if (t.type == T_UP) flag = &g_sync.hc[t.m * 8];
            else if (t.type == T_QA) flag = &g_sync.oc[(t.m * 16 + t.n) * 8]; else flag = &g_sync.done[(t.m * 5 + t.n) * 8];
            if (nb > 2) {
                bulk_wait_read<1>();
                asm volatile("mbarrier.arrive.relaxed.cluster.shared::cluster.b64 _, [%0], 4;" :: "r"(em0 + 8 * st) : "memory");
                asm volatile("mbarrier.arrive.relaxed.cluster.shared::cluster.b64 _, [%0], 4;" :: "r"(em1 + 8 * st) : "memory");
            }
            bulk_wait_read<0>();
            mbar_arrive(sb + S_BAR + MB_SEMPTY + 8 * wg);
            bulk_wait<0>();
            if (RELFLAG) red_rel_add(flag, 1); else red_rlx_add(flag, 1);
        }
        __syncwarp();
        sph ^= 1;
        if (t.type != T_UP) st = (st + 1) % G_NST;
    }
}

DEVI void softmax_rows(const float* s, uint32_t* pf, float& sum0, float& sum1, bool hi, int r0, int t) {
    float e[20];
    #pragma unroll
    for (int i = 0; i < 20; i++) e[i] = hi ? s[20 + i] : s[i];
    float m0 = fmaxf(e[0], e[1]), m1 = fmaxf(e[2], e[3]);
    #pragma unroll
    for (int i = 1; i < 5; i++) {
        const int key = (i - 1) * 8 + 2 * t;
        if (key > r0) e[4 * i] = -INFINITY;
        if (key + 1 > r0) e[4 * i + 1] = -INFINITY;
        if (key > r0 + 8) e[4 * i + 2] = -INFINITY;
        if (key + 1 > r0 + 8) e[4 * i + 3] = -INFINITY;
        m0 = fmaxf(m0, fmaxf(e[4 * i], e[4 * i + 1])); m1 = fmaxf(m1, fmaxf(e[4 * i + 2], e[4 * i + 3]));
    }
    m0 = fmaxf(m0, __shfl_xor_sync(0xffffffffu, m0, 1)); m1 = fmaxf(m1, __shfl_xor_sync(0xffffffffu, m1, 1));
    m0 = fmaxf(m0, __shfl_xor_sync(0xffffffffu, m0, 2)); m1 = fmaxf(m1, __shfl_xor_sync(0xffffffffu, m1, 2));
    const float csc = 0.08838834764831845f * 1.4426950408889634f;
    const float c0 = m0 * csc, c1 = m1 * csc;
    sum0 = 0.f; sum1 = 0.f;
    #pragma unroll
    for (int i = 0; i < 5; i++) {
        e[4 * i] = ex2(fmaf(e[4 * i], csc, -c0)); e[4 * i + 1] = ex2(fmaf(e[4 * i + 1], csc, -c0));
        e[4 * i + 2] = ex2(fmaf(e[4 * i + 2], csc, -c1)); e[4 * i + 3] = ex2(fmaf(e[4 * i + 3], csc, -c1));
        sum0 += e[4 * i] + e[4 * i + 1]; sum1 += e[4 * i + 2] + e[4 * i + 3];
    }
    #pragma unroll
    for (int i = 0; i < 5; i++) {
        const uint32_t a = pack2(e[4 * i], e[4 * i + 1]), b = pack2(e[4 * i + 2], e[4 * i + 3]);
        pf[2 * i] = hi ? 0u : a; pf[2 * i + 1] = hi ? 0u : b; pf[10 + 2 * i] = hi ? a : 0u; pf[11 + 2 * i] = hi ? b : 0u;
    }
    sum0 += __shfl_xor_sync(0xffffffffu, sum0, 1); sum1 += __shfl_xor_sync(0xffffffffu, sum1, 1);
    sum0 += __shfl_xor_sync(0xffffffffu, sum0, 2); sum1 += __shfl_xor_sync(0xffffffffu, sum1, 2);
}

template<int NU, int NS> DEVI void red_units(const unsigned char* src, bf16* out, int u0, int nsplit, int lane) {
    uint4 v[NU][NS];
    src += (u0 >> 2) * 8192 + (u0 & 3) * 512;
    #pragma unroll
    for (int z = 0; z < NU; z++)
        #pragma unroll
        for (int q = 0; q < NS; q++) v[z][q] = ld_rlx128(src + (q < NS - 1 ? q : nsplit - 1) * 65536 + (z >> 2) * 8192 + (z & 3) * 512);
    sched_fence();
    const uint32_t km = nsplit == NS ? 0xffffffffu : 0u;
    #pragma unroll
    for (int z = 0; z < NU; z++) { v[z][NS - 1].x &= km; v[z][NS - 1].y &= km; v[z][NS - 1].z &= km; v[z][NS - 1].w &= km; }
    #pragma unroll
    for (int z = 0; z < NU; z++) {
        float a[8] = {0, 0, 0, 0, 0, 0, 0, 0};
        #pragma unroll
        for (int q = 0; q < NS; q++) {
            a[0] += __uint_as_float(v[z][q].x << 16); a[1] += __uint_as_float(v[z][q].x & 0xffff0000u); a[2] += __uint_as_float(v[z][q].y << 16); a[3] += __uint_as_float(v[z][q].y & 0xffff0000u);
            a[4] += __uint_as_float(v[z][q].z << 16); a[5] += __uint_as_float(v[z][q].z & 0xffff0000u); a[6] += __uint_as_float(v[z][q].w << 16); a[7] += __uint_as_float(v[z][q].w & 0xffff0000u);
        }
        const int u = u0 + z;
        bf16* dst = out + (size_t)((u & 15) * 16) * DM + (u >> 4) * 64;
        #pragma unroll
        for (int r = 0; r < 2; r++) {
            const uint32_t m0 = movm(pack2(a[4 * r], a[4 * r + 1])), m1 = movm(pack2(a[4 * r + 2], a[4 * r + 3]));
            const int sl = (lane & 28) | ((lane & 1) * 2);
            const uint32_t x0 = __shfl_sync(0xffffffffu, m0, sl), x1 = __shfl_sync(0xffffffffu, m0, sl + 1), y0 = __shfl_sync(0xffffffffu, m1, sl), y1 = __shfl_sync(0xffffffffu, m1, sl + 1);
            *(uint2*)(dst + r * 8 * DM) = (lane & 2) ? make_uint2(y0, y1) : make_uint2(x0, x1);
        }
    }
}

DEVI void gemm_consumer(const Maps& mp, const uint32_t sb, const int warp, const int lane, const int cta, bf16* __restrict__ out) {
    const int wg = warp >> 2, wi = warp & 3, g = lane >> 2, t = lane & 3;
    const int rank = cta & 1;
    const uint32_t rel = mapa(sb + S_BAR + MB_EMPTY, lane & 1), tem0 = mapa(sb + S_BAR + MB_TEMPTY, 0);
    Pipe pp{0, 0};
    uint32_t tslot = 0, tph = 0, sph = 0;
    bool gate_ok = false;
#define TL(i)
    while (true) {
        const uint32_t task = next_task(sb, tem0, tslot, tph, lane == 0);
        if (task == 0xffffffffu) break;
        const Task tk = decode_task(task, rank);
        const int type = tk.type, m = tk.m, n = tk.n, nk = tk.nk;
        if (type == T_RED) {
            const int tile = m * 5 + n;
            if (lane == 0) wait_ge(&g_sync.done[tile * 8], 2 * tk.split);
            __syncwarp();
            TL(1);
            const int u0 = tk.k0 + (rank * 2 + wg) * nk;
            const unsigned char* src = (const unsigned char*)g_part + (size_t)part_slot(m, n) * 65536 + wi * 2048 + lane * 16;
            bf16* dst = out + (size_t)(m * 256 + g) * DM + n * 128 + wi * 16 + 4 * t;
            if (nk == 8) red_units<8, 4>(src, dst, u0, tk.split, lane); else if (nk == 4) red_units<4, 6>(src, dst, u0, tk.split, lane); else red_units<1, MAXSPLIT>(src, dst, u0, tk.split, lane);
            mbar_wait(sb + S_BAR + MB_FULL + 8 * pp.st, pp.ph);
            release_stage(rel, pp.st, lane); pipe_adv(pp);
            TL(2);
            continue;
        }
        if (tk.half && wg) {
            for (int i = 0; i <= nk; i++) { mbar_wait(sb + S_BAR + MB_FULL + 8 * pp.st, pp.ph); release_stage(rel, pp.st, lane); pipe_adv(pp); }
            continue;
        }
        uint32_t pk[64];
        float acc[128];
        if (type == T_OUT) {
            gemm_mainloop<true>(acc, sb, pp, nk, wg, lane, rel);
            TL(1);
            #pragma unroll
            for (int i = 0; i < 64; i++) pk[i] = pack2(acc[2 * i], acc[2 * i + 1]);
            dump_tile<E_RAW, 4>(pk, sb, pp, sph, wg, wi, lane);
            TL(2);
            continue;
        }
        const int row0 = m * 128 + wg * 64 + wi * 16;
        float g0 = 0.f, g1 = 0.f;
        if (type != T_KV) {
            if (!gate_ok) { if (lane == 0) wait_ge(g_sync.gate, NTOK); __syncwarp(); gate_ok = true; }
            g0 = ld_rlxf(&g_gate[row0 + g]); g1 = ld_rlxf(&g_gate[row0 + g + 8]);
        }
        gemm_mainloop<false>(acc, sb, pp, nk, wg, lane, rel);
        TL(1);
        if (type == T_UP) {
            const float s0 = 1.f - g0, s1 = 1.f - g1;
            #pragma unroll
            for (int i = 0; i < 32; i++) { const float sc = (i & 1) ? s1 : s0; pk[i] = pack2(acc[2 * i] * acc[2 * i + 64] * sc, acc[2 * i + 1] * acc[2 * i + 65] * sc); }
            dump_tile<E_ROWS, 2>(pk, sb, pp, sph, wg, wi, lane);
            TL(2);
            continue;
        }
        #pragma unroll
        for (int i = 0; i < 64; i++) pk[i] = pack2(acc[2 * i], acc[2 * i + 1]);
        if (type == T_KV) {
            dump_tile<E_ROWS, 4>(pk, sb, pp, sph, wg, wi, lane);
            TL(2);
            continue;
        }
        const bool hi = wi >= 2;
        const int r0 = (wi & 1) * 16 + g;
        float s[2][40];
        uint32_t stg_[2];
        #pragma unroll
        for (int hh = 0; hh < 2; hh++) {
            mbar_wait(sb + S_BAR + MB_FULL + 8 * pp.st, pp.ph);
            const uint64_t db = mkdesc(sb + pp.st * G_STAGE + wg * 10240, 16, 1024);
            wg_fence();
            #pragma unroll
            for (int k = 0; k < 8; k++) { if (k == 0) wg_rs80_z(s[hh], pk + hh * 32, db); else wg_rs80(s[hh], pk + hh * 32 + k * 4, db + (k >> 2) * 1280 + (k & 3) * 2, 1); }
            wg_commit();
            stg_[hh] = pp.st; pipe_adv(pp);
        }
        uint32_t pf[2][20]; float f0[2], f1[2];
        float o[2][64];
        wg_wait<1>(); release_stage(rel, stg_[0], lane);
        softmax_rows(s[0], pf[0], f0[0], f1[0], hi, r0, t);
        wg_wait<0>(); release_stage(rel, stg_[1], lane);
        #pragma unroll
        for (int hh = 0; hh < 2; hh++) {
            if (hh == 1) softmax_rows(s[1], pf[1], f0[1], f1[1], hi, r0, t);
            mbar_wait(sb + S_BAR + MB_FULL + 8 * pp.st, pp.ph);
            const uint64_t db = mkdesc(sb + pp.st * G_STAGE + wg * 10240, 20480, 1024);
            #pragma unroll
            for (int i = 0; i < 20; i++) asm volatile("mov.b32 %0, %0;" : "+r"(pf[hh][i]));
            sched_fence();
            wg_fence();
            #pragma unroll
            for (int k = 0; k < 5; k++) { if (k == 0) wg_rs128t_z(o[hh], pf[hh], db); else wg_rs128t(o[hh], pf[hh] + k * 4, db + k * 128, 1); }
            wg_commit();
            sched_fence();
            stg_[hh] = pp.st; pipe_adv(pp);
        }
        #pragma unroll
        for (int hh = 0; hh < 2; hh++) {
            if (hh == 0) wg_wait<1>(); else wg_wait<0>();
            release_stage(rel, stg_[hh], lane);
            const float a0 = __fdividef(g0, f0[hh]), a1 = __fdividef(g1, f1[hh]);
            #pragma unroll
            for (int i = 0; i < 32; i++) { const float sc = (i & 1) ? a1 : a0; pk[hh * 32 + i] = pack2(o[hh][2 * i] * sc, o[hh][2 * i + 1] * sc); }
        }
        dump_tile<E_ROWS, 4>(pk, sb, pp, sph, wg, wi, lane);
        TL(2);
    }
}

DEVI void gate_rows(const bf16* __restrict__ x, const bf16* __restrict__ gw, int wid, int nw, int lane) {
    for (int r0 = wid * 4; r0 < NTOK; r0 += nw * 4) {
        const int r = r0 + (lane >> 3);
        uint4 xv[10];
        #pragma unroll
        for (int i = 0; i < 10; i++) xv[i] = *(const uint4*)(x + (size_t)r * DM + i * 64 + (lane & 7) * 8);
        float a = 0.f;
        #pragma unroll
        for (int i = 0; i < 10; i++) {
            const uint4 wv = *(const uint4*)(gw + i * 64 + (lane & 7) * 8);
            a += __uint_as_float(xv[i].x << 16) * __uint_as_float(wv.x << 16) + __uint_as_float(xv[i].x & 0xffff0000u) * __uint_as_float(wv.x & 0xffff0000u)
               + __uint_as_float(xv[i].y << 16) * __uint_as_float(wv.y << 16) + __uint_as_float(xv[i].y & 0xffff0000u) * __uint_as_float(wv.y & 0xffff0000u)
               + __uint_as_float(xv[i].z << 16) * __uint_as_float(wv.z << 16) + __uint_as_float(xv[i].z & 0xffff0000u) * __uint_as_float(wv.z & 0xffff0000u)
               + __uint_as_float(xv[i].w << 16) * __uint_as_float(wv.w << 16) + __uint_as_float(xv[i].w & 0xffff0000u) * __uint_as_float(wv.w & 0xffff0000u);
        }
        a += __shfl_xor_sync(0xffffffffu, a, 1); a += __shfl_xor_sync(0xffffffffu, a, 2); a += __shfl_xor_sync(0xffffffffu, a, 4);
        if ((lane & 7) == 0) g_gate[r] = 1.f / (1.f + __expf(-a));
    }
}

DEVI void chain_cleanup(unsigned char* xb, int lane) {
    uint32_t last = 0;
    if (lane == 0) last = atomicAdd(g_sync.chain_exit, 1) == 63;
    if (uni(last)) {
        #pragma unroll 1
        for (int q = 0; q < 16; q++) {
            uint4* pg = (uint4*)(xb + 8 * XREG + (q < 8 ? xoff_i(q >> 1) + ((NSEG - 2) & 3) * 16384 : xoff_i(4) + ((q >> 1) & 3) * 16384) + (q & 1) * 4096);
            #pragma unroll
            for (int i = 0; i < 5; i++) pg[lane + 32 * i] = make_uint4(0, 0, 0, 0);
        }
    }
}
DEVI void finish_cta(int lane) {
    uint32_t last = 0;
    if (lane == 0) last = atomicAdd(g_sync.exitc, 1) == 131;
    if (uni(last)) {
        uint4* p = (uint4*)&g_sync;
        for (int i = lane; i < (int)(sizeof(Sync) / 16); i += 32) p[i] = make_uint4(0, 0, 0, 0);
    }
}

__global__ void __cluster_dims__(2, 1, 1) __launch_bounds__(384, 1)
fused_kernel(const __grid_constant__ Maps mp, const bf16* __restrict__ x, const bf16* __restrict__ mem0, const bf16* __restrict__ gw, unsigned char* __restrict__ xb, bf16* __restrict__ out)
{
    extern __shared__ __align__(1024) unsigned char smem_raw[];
    const uint32_t sb = smem_u32(smem_raw);
    const int tid = threadIdx.x, warp = __shfl_sync(0xffffffffu, tid >> 5, 0), lane = tid & 31;
    if (tid == 0) {
        mbar_init(sb + S_BAR + MB_W0, 1); mbar_init(sb + S_BAR + MB_W1, 1); mbar_init(sb + S_BAR + MB_S, 1); mbar_init(sb + S_BAR + MB_V, 1);
        mbar_init(sb + S_BAR + MB_KX, 1);
        for (int i = 0; i < G_NST; i++) { mbar_init(sb + S_BAR + MB_FULL + 8 * i, 1); mbar_init(sb + S_BAR + MB_EMPTY + 8 * i, 16); }
        for (int i = 0; i < TQN; i++) { mbar_init(sb + S_BAR + MB_TFULL + 8 * i, 1); mbar_init(sb + S_BAR + MB_TEMPTY + 8 * i, 21); }
        for (int i = 0; i < 2; i++) { mbar_init(sb + S_BAR + MB_SFULL + 8 * i, 4); mbar_init(sb + S_BAR + MB_SEMPTY + 8 * i, 1); }
        asm volatile("fence.mbarrier_init.release.cluster;" ::: "memory");
    }
    const int j = blockIdx.x & 1;
    const int cl = blockIdx.x >> 1;
    if (warp == 1 && (j == 0 || cl < 9)) {
        unsigned char* pp = xb + 8 * XREG + 0x180000 + blockIdx.x * 16 + j * 2048;
        if (lane < 4) st_rlx128(pp - (j ? 16 : 0) + (lane >> 1) * 4096 + (lane & 1) * 16, make_uint4(0, 0, 0, 0));
        else if (lane < 8 && j) st_rlx128(xb + cl * XREG + ((lane >> 1) & 1) * 4096 + (lane & 1) * 16, make_uint4(0, 0, 0, 0));
        uint32_t old = lane == 8 ? ld_rlx32(g_sync.sidecnt) : 0;
        __syncwarp();
        if (lane == 0) {
            ST(0);
            const uint32_t side = probe_near<3>(pp, sb + S_BAR + 200);
            if (j) st_rlx32(&g_sync.side[cl], 2 + (side ^ probe_near<3>(xb + cl * XREG, sb + S_BAR + 200)));
            else {
                ST(1);
                old = atomicAdd(g_sync.sidecnt, side ? 0x10000u : 1u);
                const uint32_t tk = side ? old >> 16 : old & 0xffff;
                uint32_t c; int it = 0;
                do { c = ld_rlx32(g_sync.sidecnt); spin_guard(it); } while ((c & 0xffff) + (c >> 16) < 66);
                const uint32_t n0 = c & 0xffff, maj = n0 >= 33 ? 0 : 1, nmaj = maj ? c >> 16 : n0;
                ST(3);
                sts32u(sb + S_BAR + 192, (side == maj ? tk : nmaj + tk) | (maj << 8));
            }
        }
    }
    if (warp >= 4 && warp < 8 && blockIdx.x < 128) gate_rows(x, gw, blockIdx.x * 4 + warp - 4, 512, lane);
    if (warp == 3) {
        if (lane < (int)(sizeof(Maps) / 128)) asm volatile("prefetch.tensormap [%0];" :: "l"((const char*)&mp + lane * 128) : "memory");
        if (lane == 31) sts32u(sb + S_BAR + 204, c_tasks[cl >> 1] + ld_rlx32(g_sync.queue));
    }
    __syncthreads();
    asm volatile("barrier.cluster.arrive.relaxed.aligned; barrier.cluster.wait.aligned;" ::: "memory");
    uint32_t role_;
    asm volatile("ld.volatile.shared::cluster.u32 %0, [%1];" : "=r"(role_) : "r"(mapa(sb + S_BAR + 192, 0)) : "memory");
    role_ = uni(role_);
    const int role = role_ & 255, maj = role_ >> 8;
    if (tid == 320 && blockIdx.x < 128) red_rel_add(g_sync.gate, 16);
    const int cta = role * 2 + j;
    if (tid == 0) { ST(4); }
    const int h = role;
    if (warp >= 8) {
        asm volatile("setmaxnreg.dec.sync.aligned.u32 %0;" :: "n"(RH));
        if (role < 32) {
            if (!NOCHAIN) chain_aux(mp, sb, warp, lane, h, j, xb, mem0, maj);
            fence_async_smem();
            asm volatile("barrier.cluster.arrive.aligned; barrier.cluster.wait.aligned;" ::: "memory");
            if (warp == 11) chain_cleanup(xb, lane);
        }
        if (PREF && role >= 34 && warp == 11 && lane < 6) tma_pf2d(j ? &mp.wvC : &mp.wkC, (65 - role) * 128 + (lane & 1) * 64, (2 + (lane >> 1)) * 128);
        if (role >= 32 || JOIN) {
            if (warp == 8) { if (lane == 0) gemm_producer(mp, sb, j, role); __syncwarp(); }
            else if (warp < 11) gemm_storer(mp, sb, warp - 9, lane, j);
        }
        asm volatile("barrier.cluster.arrive.aligned; barrier.cluster.wait.aligned;" ::: "memory");
        if (warp == 8) finish_cta(lane);
    } else {
        asm volatile("setmaxnreg.inc.sync.aligned.u32 %0;" :: "n"(RM));
        if (role < 32) {
            if (NOCHAIN) {}
            else if (warp < 4) chain_main<0, false>(mp, sb, warp, lane, h, j, xb, maj);
            else if (warp < 7) chain_main<1, false>(mp, sb, warp, lane, h, j, xb, maj);
            else chain_main<1, true>(mp, sb, warp, lane, h, j, xb, maj);
            fence_async_smem();
            asm volatile("barrier.cluster.arrive.aligned; barrier.cluster.wait.aligned;" ::: "memory");
        }
        if (role >= 32 || JOIN) gemm_consumer(mp, sb, warp, lane, cta, out);
        asm volatile("barrier.cluster.arrive.aligned; barrier.cluster.wait.aligned;" ::: "memory");
    }
}

typedef CUresult (*EncodeFn)(CUtensorMap*, CUtensorMapDataType, cuuint32_t, void*, const cuuint64_t*, const cuuint64_t*, const cuuint32_t*, const cuuint32_t*, CUtensorMapInterleave, CUtensorMapSwizzle, CUtensorMapL2promotion, CUtensorMapFloatOOBfill);
static void enc2d(EncodeFn fn, CUtensorMap* m, const void* base, uint64_t rows, uint64_t cols, uint32_t bc, uint32_t br, bool swz = true) {
    cuuint64_t dims[2] = {cols, rows}; cuuint64_t strides[1] = {cols * 2}; cuuint32_t box[2] = {bc, br}; cuuint32_t es[2] = {1, 1};
    fn(m, CU_TENSOR_MAP_DATA_TYPE_BFLOAT16, 2, (void*)base, dims, strides, box, es, CU_TENSOR_MAP_INTERLEAVE_NONE, swz ? CU_TENSOR_MAP_SWIZZLE_128B : CU_TENSOR_MAP_SWIZZLE_NONE, CU_TENSOR_MAP_L2_PROMOTION_L2_256B, CU_TENSOR_MAP_FLOAT_OOB_FILL_NONE);
}

extern "C" void kernel_launch(void* const* d_in, const int* in_sizes, int n_in, void* d_out, int out_size) {
    const bf16* x = (const bf16*)d_in[0]; const bf16* mem0 = (const bf16*)d_in[1];
    const bf16 *Wq = (const bf16*)d_in[2], *Wk = (const bf16*)d_in[3], *Wv = (const bf16*)d_in[4], *Wo = (const bf16*)d_in[5];
    const bf16 *Wg = (const bf16*)d_in[8], *Wu = (const bf16*)d_in[9], *Wd = (const bf16*)d_in[10], *gw = (const bf16*)d_in[11];
    void* p = nullptr; cudaDriverEntryPointQueryResult st;
    cudaGetDriverEntryPoint("cuTensorMapEncodeTiled", &p, cudaEnableDefault, &st);
    EncodeFn fn = (EncodeFn)p;
    void *kv, *ah, *xraw;
    cudaGetSymbolAddress(&kv, g_KV); cudaGetSymbolAddress(&ah, g_AH); cudaGetSymbolAddress(&xraw, g_xbuf);
    unsigned char* xb = (unsigned char*)(((uintptr_t)xraw + 0x1FFFFF) & ~(uintptr_t)0x1FFFFF);
    Maps mp;
    enc2d(fn, &mp.x, x, NTOK, DM, 64, 128);
    enc2d(fn, &mp.wq, Wq, DM, HD, 64, 64); enc2d(fn, &mp.wk, Wk, DM, HD, 64, 64); enc2d(fn, &mp.wv, Wv, DM, HD, 64, 64);
    enc2d(fn, &mp.wg, Wg, DM, FF, 64, 64); enc2d(fn, &mp.wu, Wu, DM, FF, 64, 64);
    enc2d(fn, &mp.wo, Wo, HD, DM, 64, 64); enc2d(fn, &mp.wd, Wd, FF, DM, 64, 64);
    enc2d(fn, &mp.ahL, ah, NTOK, AHW, 64, 128); enc2d(fn, &mp.ahS, ah, NTOK, AHW, 64, 64);
    enc2d(fn, &mp.kvA, kv, NSEG * SEGROWS, KVW, 64, 160); enc2d(fn, &mp.kvC, kv, NSEG * SEGROWS, KVW, 64, 32);
    enc2d(fn, &mp.kvE, kv, NSEG * SEGROWS, KVW, 64, 8);
    enc2d(fn, &mp.wqC, Wq, DM, HD, 64, 128); enc2d(fn, &mp.wkC, Wk, DM, HD, 64, 128); enc2d(fn, &mp.wvC, Wv, DM, HD, 64, 128);
    enc2d(fn, &mp.woC, Wo, HD, DM, 64, 128);
    cudaFuncSetAttribute(fused_kernel, cudaFuncAttributeMaxDynamicSharedMemorySize, S_TOTAL);
    fused_kernel<<<132, 384, S_TOTAL>>>(mp, x, mem0, gw, xb, (bf16*)d_out);
}
```
